```python
import torch

def _softmax(x, axis=-1):
    return torch.softmax(x, dim=axis)
def _gelu(x):
    return torch.nn.functional.gelu(x, approximate="tanh")
def _silu(x):
    return torch.nn.functional.silu(x)
def _sigmoid(x):
    return torch.sigmoid(x)
def _layernorm(x, axis=-1, eps=1e-5):
    m = x.mean(dim=axis, keepdim=True)
    v = x.var(dim=axis, keepdim=True, unbiased=False)
    return (x - m) / torch.sqrt(v + eps)
def _scatter_add(tgt, idx, src, axis=0):
    return tgt.clone().index_add_(axis, idx, src)
def _segment_sum(src, seg, n):
    out = torch.zeros((n,) + src.shape[1:], dtype=src.dtype)
    return out.index_add_(0, seg, src)
def _pad(x, pw):
    flat = tuple(v for pair in reversed(pw) for v in pair)
    return torch.nn.functional.pad(x, flat)

kernel_name = 'parallel_sum__ssm_conv_s5__glu_gated_glu__prompt'

def setup_inputs():

    _w = (lambda a: (lambda t: t.to(torch.bfloat16) if t.is_floating_point() else t)(torch.as_tensor(a)))
    def _A_setup():
        B, S, D = 1, 2048, 576
        P = D
        Lambda_re = -0.5 * (lambda _x: torch.exp(torch.as_tensor(_x)))((lambda *s: torch.randn(*s, dtype=torch.bfloat16) * 0.8)(P))
        Lambda_im = (lambda *s: torch.randn(*s, dtype=torch.bfloat16) * 0.8)(P) * 1.0
        B_re = (lambda *s: torch.randn(*s, dtype=torch.bfloat16) * 0.8)(P, D) * (D ** -0.5)
        B_im = (lambda *s: torch.randn(*s, dtype=torch.bfloat16) * 0.8)(P, D) * (D ** -0.5)
        C_re = (lambda *s: torch.randn(*s, dtype=torch.bfloat16) * 0.8)(D, P) * (P ** -0.5)
        C_im = (lambda *s: torch.randn(*s, dtype=torch.bfloat16) * 0.8)(D, P) * (P ** -0.5)
        log_dt = (lambda *s: torch.randn(*s, dtype=torch.bfloat16) * 0.8)(P) * 0.3 - 2.0
        Dskip = (lambda *s: torch.randn(*s, dtype=torch.bfloat16) * 0.8)(D)
        return {
            "x": _w((lambda *s: torch.randn(*s, dtype=torch.bfloat16) * 0.05)(B, S, D)),
            "Lambda_re": _w(Lambda_re),
            "Lambda_im": _w(Lambda_im),
            "B_re": _w(B_re),
            "B_im": _w(B_im),
            "C_re": _w(C_re),
            "C_im": _w(C_im),
            "log_dt": _w(log_dt),
            "Dskip": _w(Dskip),
        }
    _A_in = _A_setup()

    def _B_setup():
        B, S, D, F = 1, 2048, 576, 4608
        return {
            "x": _w((lambda *s: torch.randn(*s, dtype=torch.bfloat16) * 0.05)(B, S, D)),
            "w_gate": _w((lambda *s: torch.randn(*s, dtype=torch.bfloat16) * 0.05)(D, F)),
            "w_up": _w((lambda *s: torch.randn(*s, dtype=torch.bfloat16) * 0.05)(D, F)),
            "w_down": _w((lambda *s: torch.randn(*s, dtype=torch.bfloat16) * 0.05)(F, D)),
        }
    _B_in = _B_setup()

    return {
        "A_x": _A_in["x"],
        "A_Lambda_re": _A_in["Lambda_re"],
        "A_Lambda_im": _A_in["Lambda_im"],
        "A_B_re": _A_in["B_re"],
        "A_B_im": _A_in["B_im"],
        "A_C_re": _A_in["C_re"],
        "A_C_im": _A_in["C_im"],
        "A_log_dt": _A_in["log_dt"],
        "A_Dskip": _A_in["Dskip"],
        "B_x": _B_in["x"],
        "B_w_gate": _B_in["w_gate"],
        "B_w_up": _B_in["w_up"],
        "B_w_down": _B_in["w_down"],
    }

def reference(A_x, A_Lambda_re, A_Lambda_im, A_B_re, A_B_im, A_C_re, A_C_im, A_log_dt, A_Dskip, B_x, B_w_gate, B_w_up, B_w_down):
    def _A_ref(x, Lambda_re, Lambda_im, B_re, B_im, C_re, C_im, log_dt, Dskip):
        Bsz, L, H = x.shape
        Lam = Lambda_re + 1j * Lambda_im
        Bmat = B_re + 1j * B_im
        Cmat = C_re + 1j * C_im
        dt = torch.exp(log_dt)
        Lam_bar = torch.exp(dt * Lam)
        B_bar = ((Lam_bar - 1.0) / Lam)[:, None] * Bmat
        Bu = torch.einsum("bld,pd->blp", x + 0j, B_bar)
        h = torch.zeros_like(Bu[:, 0, :])
        hs = []
        for t in range(L):
            h = Lam_bar[None, :] * h + Bu[:, t, :]
            hs.append(h)
        hseq = torch.stack(hs, 1)
        y = 2.0 * torch.einsum("blp,dp->bld", hseq, Cmat).real + x * Dskip[None, None, :]
        return y

    def _B_ref(x, w_gate, w_up, w_down):
        g = torch.einsum("bsd,df->bsf", x, w_gate)
        u = torch.einsum("bsd,df->bsf", x, w_up)
        h = _sigmoid(g) * u
        return torch.einsum("bsf,fd->bsd", h, w_down)

    x = A_x
    xn = _layernorm(x, axis=-1)
    return x + _A_ref(xn, A_Lambda_re, A_Lambda_im, A_B_re, A_B_im, A_C_re, A_C_im, A_log_dt, A_Dskip) + _B_ref(xn, B_w_gate, B_w_up, B_w_down)
```

```cpp
#include <cuda_runtime.h>
#include <cuda_bf16.h>
#include <cuda.h>
#include <stdint.h>
#include <string.h>

namespace {

constexpr int SEQ = 2048, DM = 576, FF = 4608;
constexpr uint32_t UNIT = 8192, WREG = 10 * UNIT;
constexpr int NSLOT = 144, NSLOT_SP = 48;
constexpr int SMEM_BYTES = 232448;
constexpr uint32_t sb = 1024;
constexpr uint32_t OFF_STATS = sb + 28 * UNIT;
constexpr uint32_t OFF_DSK = OFF_STATS + 1024;
constexpr uint32_t BAR_FULL = OFF_DSK + 256;
constexpr uint32_t BAR_EMPTY = BAR_FULL + 14 * 8;
constexpr uint32_t BAR_X = BAR_EMPTY + 14 * 8;
constexpr uint32_t BAR_STASH = BAR_X + 6 * 8;
constexpr uint32_t BAR_P1 = BAR_STASH + 8;
constexpr uint32_t BAR_SCAN = BAR_P1 + 8;
constexpr uint32_t BAR_G8 = BAR_SCAN + 8;
constexpr uint32_t BAR_PAR = BAR_G8 + 8;
constexpr uint32_t BAR_DONE = BAR_PAR + 8;
constexpr uint32_t OFF_PAR = BAR_DONE + 8;
constexpr int NTHREADS = 384;
#define SKEW 3
#define SKEW2 2
#define X_NADD 2
#define X_NA8 8
#define PF_NS 500
#define SEND_PACE
#define SEND_B 8192
#define SKEW5 1
#define PF_NS2 1000
#define EV1 9
#define EV2 10
#define XPRI -1
#define P5S 2
#define P5R 5
#define P5A 0
#define FLAGBAR BAR_P1
#define XKK 6
#define XPS 0
#define SK0 6
#define SK1 6
#define RG2 96
#define STG_AT 2
#define LAG2 1
#define XAT 0
#define PF_BAR 5
#define SCANT 6
#define EXT2_UNTIL 46
#define EXT1_UNTIL 29

struct Params {
  CUtensorMap x, x2, wg, wu, wd, bre, bim, cre, cim, hs;
  const __nv_bfloat16 *xg, *lam_re, *lam_im, *log_dt, *dskip;
  float* out;
  uint32_t zero;
  uint8_t sched[NSLOT + 2];
  uint8_t sched_sp[NSLOT_SP];
  uint8_t reclaim[2][8];
};

__device__ uint4 g_part[16 * 9 * 9 * 1024];
__device__ uint2 g_state[9 * 16 * 64];
__device__ uint2 g_stats[SEQ];
__device__ __nv_bfloat16 g_hs[SEQ * 1152];
__device__ uint32_t g_flag[16];
__device__ uint32_t g_epoch[132];
#define PCLK "%%globaltimer_lo"
#define PROBE(w, n)
#define CPROBE(n)
#define PROF_DUMP()
#define TR(slot, k)

constexpr uint64_t EVICT_FIRST = 0x12F0000000000000ull;
__device__ __forceinline__ void mbar_init(uint32_t bar, uint32_t cnt) { asm volatile("mbarrier.init.shared::cta.b64 [%0], %1;" ::"r"(bar), "r"(cnt) : "memory"); }
__device__ __forceinline__ void mbar_expect_tx(uint32_t bar, uint32_t bytes) { asm volatile("mbarrier.arrive.expect_tx.shared::cta.b64 _, [%0], %1;" ::"r"(bar), "r"(bytes) : "memory"); }
__device__ __forceinline__ void mbar_arrive(uint32_t bar) { asm volatile("mbarrier.arrive.shared::cta.b64 _, [%0];" ::"r"(bar) : "memory"); }
__device__ __forceinline__ void mbar_arrive_w(uint32_t bar) {
  asm volatile("{\n.reg .pred p;\nelect.sync _|p, 0xffffffff;\n@p mbarrier.arrive.shared::cta.b64 _, [%0];\n}" ::"r"(bar) : "memory");
}
__device__ __forceinline__ void mbar_wait(uint32_t bar, uint32_t parity) {
  asm volatile("{\n.reg .pred p;\nLOOP:\nmbarrier.try_wait.parity.shared::cta.b64 p, [%0], %1;\n@!p bra LOOP;\n}" ::"r"(bar), "r"(parity) : "memory");
}
__device__ __forceinline__ void mbar_wait_b(uint32_t bar, uint32_t parity) {
  asm volatile(
      "{\n.reg .pred p;\n.reg .u32 c;\nmov.u32 c, 0;\n"
      "LOOP:\nmbarrier.try_wait.parity.shared::cta.b64 p, [%0], %1;\n@p bra DONE;\n"
      "add.u32 c, c, 1;\nsetp.lt.u32 p, c, 0x2000000;\n@p bra LOOP;\ntrap;\nDONE:\n}" ::"r"(bar), "r"(parity) : "memory");
}
__device__ __forceinline__ void mbar_wait_slow(uint32_t bar, uint32_t parity) {
  asm volatile(
      "{\n.reg .pred p;\n.reg .u32 c;\nmov.u32 c, 0;\n"
      "LOOP:\nmbarrier.test_wait.parity.shared::cta.b64 p, [%0], %1;\n@p bra DONE;\nnanosleep.u32 256;\n"
      "add.u32 c, c, 1;\nsetp.lt.u32 p, c, 0x400000;\n@p bra LOOP;\ntrap;\nDONE:\n}" ::"r"(bar), "r"(parity) : "memory");
}
__device__ __forceinline__ void tma_load(uint32_t dst, const CUtensorMap* map, int c0, int c1, uint32_t bar) {
  asm volatile("cp.async.bulk.tensor.2d.shared::cluster.global.mbarrier::complete_tx::bytes [%0], [%1, {%3, %4}], [%2];"
               ::"r"(dst), "l"(map), "r"(bar), "r"(c0), "r"(c1) : "memory");
}
__device__ __forceinline__ void tma_load3(uint32_t dst, const CUtensorMap* map, int c0, int c1, int c2, uint32_t bar) {
  asm volatile("cp.async.bulk.tensor.3d.shared::cluster.global.mbarrier::complete_tx::bytes [%0], [%1, {%3, %4, %5}], [%2];"
               ::"r"(dst), "l"(map), "r"(bar), "r"(c0), "r"(c1), "r"(c2) : "memory");
}
__device__ __forceinline__ void tma_prefetch(const CUtensorMap* map, int c0, int c1) {
  asm volatile("cp.async.bulk.prefetch.tensor.2d.L2.global [%0, {%1, %2}];" ::"l"(map), "r"(c0), "r"(c1) : "memory");
}
__device__ __forceinline__ void fence_async() { asm volatile("fence.proxy.async.shared::cta;" ::: "memory"); }
__device__ __forceinline__ void fence_init() { asm volatile("fence.mbarrier_init.release.cluster;" ::: "memory"); }
__device__ __forceinline__ void fence_async_all() { asm volatile("fence.proxy.async;" ::: "memory"); }
__device__ __forceinline__ void bar_sync(int id, int n) { asm volatile("bar.sync %0, %1;" ::"r"(id), "r"(n) : "memory"); }
__device__ __forceinline__ void bar_arrive(int id, int n) { asm volatile("bar.arrive %0, %1;" ::"r"(id), "r"(n) : "memory"); }
__device__ __forceinline__ void wg_fence() { asm volatile("wgmma.fence.sync.aligned;" ::: "memory"); }
__device__ __forceinline__ void wg_commit() { asm volatile("wgmma.commit_group.sync.aligned;" ::: "memory"); }
template <int N> __device__ __forceinline__ void wg_wait() { asm volatile("wgmma.wait_group.sync.aligned %0;" ::"n"(N) : "memory"); }
template <int N> __device__ __forceinline__ void fence_regs(float (&a)[N]) {
#pragma unroll
  for (int i = 0; i < N; i++) asm volatile("" : "+f"(a[i])::"memory");
}
__device__ __forceinline__ void ldsm4(uint32_t* r, uint32_t addr) {
  asm volatile("ldmatrix.sync.aligned.m8n8.x4.shared.b16 {%0,%1,%2,%3}, [%4];" : "=r"(r[0]), "=r"(r[1]), "=r"(r[2]), "=r"(r[3]) : "r"(addr) : "memory");
}
__device__ __forceinline__ void stsm4(uint32_t addr, const uint32_t* r) {
  asm volatile("stmatrix.sync.aligned.m8n8.x4.shared.b16 [%0], {%1,%2,%3,%4};" ::"r"(addr), "r"(r[0]), "r"(r[1]), "r"(r[2]), "r"(r[3]) : "memory");
}
__device__ __forceinline__ void sts32(uint32_t addr, uint32_t a) { asm volatile("st.shared.b32 [%0], %1;" ::"r"(addr), "r"(a) : "memory"); }
__device__ __forceinline__ void sts64(uint32_t addr, uint32_t a, uint32_t b) { asm volatile("st.shared.v2.b32 [%0], {%1,%2};" ::"r"(addr), "r"(a), "r"(b) : "memory"); }
__device__ __forceinline__ void sts128(uint32_t addr, uint32_t a, uint32_t b, uint32_t c, uint32_t d) {
  asm volatile("st.shared.v4.b32 [%0], {%1,%2,%3,%4};" ::"r"(addr), "r"(a), "r"(b), "r"(c), "r"(d) : "memory");
}
__device__ __forceinline__ uint32_t lds32(uint32_t addr) { uint32_t v; asm volatile("ld.shared.b32 %0, [%1];" : "=r"(v) : "r"(addr) : "memory"); return v; }
__device__ __forceinline__ uint2 lds64(uint32_t addr) { uint2 v; asm volatile("ld.shared.v2.b32 {%0,%1}, [%2];" : "=r"(v.x), "=r"(v.y) : "r"(addr) : "memory"); return v; }
__device__ __forceinline__ float2 lds64f(uint32_t addr) { float2 v; asm volatile("ld.shared.v2.f32 {%0,%1}, [%2];" : "=f"(v.x), "=f"(v.y) : "r"(addr) : "memory"); return v; }
__device__ __forceinline__ void ld_tag16(uint32_t* r, const uint4* p) {
  asm volatile("{\n.reg .b128 t;\nld.relaxed.gpu.global.b128 t, [%4];\nmov.b128 {%0,%1,%2,%3}, t;\n}" : "=r"(r[0]), "=r"(r[1]), "=r"(r[2]), "=r"(r[3]) : "l"(p) : "memory");
}
__device__ __forceinline__ uint2 ld_tag8(const uint2* p) {
  uint2 r;
  asm volatile("{\n.reg .b64 t;\nld.relaxed.gpu.global.b64 t, [%2];\nmov.b64 {%0,%1}, t;\n}" : "=r"(r.x), "=r"(r.y) : "l"(p) : "memory");
  return r;
}
__device__ __forceinline__ void st_tag16(uint4* p, const uint32_t* r) {
  asm volatile("{\n.reg .b128 t;\nmov.b128 t, {%1,%2,%3,%4};\nst.relaxed.gpu.global.b128 [%0], t;\n}" ::"l"(p), "r"(r[0]), "r"(r[1]), "r"(r[2]), "r"(r[3]) : "memory");
}
__device__ __forceinline__ void st_tag8(uint2* p, uint32_t a, uint32_t b) {
  asm volatile("{\n.reg .b64 t;\nmov.b64 t, {%1,%2};\nst.relaxed.gpu.global.b64 [%0], t;\n}" ::"l"(p), "r"(a), "r"(b) : "memory");
}
__device__ __forceinline__ uint32_t pack2(float lo, float hi) { uint32_t r; asm("cvt.rn.bf16x2.f32 %0, %1, %2;" : "=r"(r) : "f"(hi), "f"(lo)); return r; }
__device__ __forceinline__ float bf_lo(uint32_t v) { return __uint_as_float(v << 16); }
__device__ __forceinline__ float bf_hi(uint32_t v) { return __uint_as_float(v & 0xffff0000u); }
__device__ __forceinline__ float bf_round(float v) { return __bfloat162float(__float2bfloat16_rn(v)); }
__device__ __forceinline__ uint32_t hsub2(uint32_t a, uint32_t b) { uint32_t r; asm("sub.rn.bf16x2 %0, %1, %2;" : "=r"(r) : "r"(a), "r"(b)); return r; }
__device__ __forceinline__ uint32_t hmul2(uint32_t a, uint32_t b) { uint32_t r; asm("mul.rn.bf16x2 %0, %1, %2;" : "=r"(r) : "r"(a), "r"(b)); return r; }
__device__ __forceinline__ uint32_t hadd2(uint32_t a, uint32_t b) { uint32_t r; asm("add.rn.bf16x2 %0, %1, %2;" : "=r"(r) : "r"(a), "r"(b)); return r; }
__device__ __forceinline__ uint32_t hfma2(uint32_t a, uint32_t b, uint32_t c) { uint32_t r; asm("fma.rn.bf16x2 %0, %1, %2, %3;" : "=r"(r) : "r"(a), "r"(b), "r"(c)); return r; }
__device__ __forceinline__ float tanh_hw(float x) { float r; asm("tanh.approx.f32 %0, %1;" : "=f"(r) : "f"(x)); return r; }
__device__ __forceinline__ uint32_t get_par() { mbar_wait(BAR_PAR, 0); return lds32(OFF_PAR); }

__device__ __forceinline__ uint32_t desc_k(uint32_t addr) { return (addr >> 4) | (1u << 16); }
__device__ __forceinline__ uint32_t desc_mn(uint32_t addr) { return (addr >> 4) | ((8192u >> 4) << 16); }

template <int TB> __device__ __forceinline__ void wgmma_rs_n128(float (&d)[64], const uint32_t* a, uint32_t db, int ob, int sd) {
  asm volatile("{\n.reg .pred p;\n.reg .b32 t;\n.reg .b64 b;\nsetp.ne.b32 p, %70, 0;\nadd.u32 t, %68, %69;\nmov.b64 b, {t, 0x40000040};\n"
    "wgmma.mma_async.sync.aligned.m64n128k16.f32.bf16.bf16 {%0,%1,%2,%3,%4,%5,%6,%7,%8,%9,%10,%11,%12,%13,%14,%15,%16,%17,%18,%19,%20,%21,%22,%23,%24,%25,%26,%27,%28,%29,%30,%31,%32,%33,%34,%35,%36,%37,%38,%39,%40,%41,%42,%43,%44,%45,%46,%47,%48,%49,%50,%51,%52,%53,%54,%55,%56,%57,%58,%59,%60,%61,%62,%63}, "
    "{%64,%65,%66,%67}, b, p, 1, 1, %71;\n}"
    : "+f"(d[0]),"+f"(d[1]),"+f"(d[2]),"+f"(d[3]),"+f"(d[4]),"+f"(d[5]),"+f"(d[6]),"+f"(d[7]),"+f"(d[8]),"+f"(d[9]),"+f"(d[10]),"+f"(d[11]),"+f"(d[12]),"+f"(d[13]),"+f"(d[14]),"+f"(d[15]),"+f"(d[16]),"+f"(d[17]),"+f"(d[18]),"+f"(d[19]),"+f"(d[20]),"+f"(d[21]),"+f"(d[22]),"+f"(d[23]),"+f"(d[24]),"+f"(d[25]),"+f"(d[26]),"+f"(d[27]),"+f"(d[28]),"+f"(d[29]),"+f"(d[30]),"+f"(d[31]),"+f"(d[32]),"+f"(d[33]),"+f"(d[34]),"+f"(d[35]),"+f"(d[36]),"+f"(d[37]),"+f"(d[38]),"+f"(d[39]),"+f"(d[40]),"+f"(d[41]),"+f"(d[42]),"+f"(d[43]),"+f"(d[44]),"+f"(d[45]),"+f"(d[46]),"+f"(d[47]),"+f"(d[48]),"+f"(d[49]),"+f"(d[50]),"+f"(d[51]),"+f"(d[52]),"+f"(d[53]),"+f"(d[54]),"+f"(d[55]),"+f"(d[56]),"+f"(d[57]),"+f"(d[58]),"+f"(d[59]),"+f"(d[60]),"+f"(d[61]),"+f"(d[62]),"+f"(d[63])
    : "r"(a[0]), "r"(a[1]), "r"(a[2]), "r"(a[3]), "r"(db), "r"(ob), "r"(sd), "n"(TB));
}
template <int TB> __device__ __forceinline__ void wgmma_ss_n128(float (&d)[64], uint32_t da, int oa, uint32_t db, int ob, int sd) {
  asm volatile("{\n.reg .pred p;\n.reg .b32 t, u;\n.reg .b64 a, b;\nsetp.ne.b32 p, %68, 0;\nadd.u32 u, %64, %65;\nmov.b64 a, {u, 0x40000040};\nadd.u32 t, %66, %67;\nmov.b64 b, {t, 0x40000040};\n"
    "wgmma.mma_async.sync.aligned.m64n128k16.f32.bf16.bf16 {%0,%1,%2,%3,%4,%5,%6,%7,%8,%9,%10,%11,%12,%13,%14,%15,%16,%17,%18,%19,%20,%21,%22,%23,%24,%25,%26,%27,%28,%29,%30,%31,%32,%33,%34,%35,%36,%37,%38,%39,%40,%41,%42,%43,%44,%45,%46,%47,%48,%49,%50,%51,%52,%53,%54,%55,%56,%57,%58,%59,%60,%61,%62,%63}, "
    "a, b, p, 1, 1, 0, %69;\n}"
    : "+f"(d[0]),"+f"(d[1]),"+f"(d[2]),"+f"(d[3]),"+f"(d[4]),"+f"(d[5]),"+f"(d[6]),"+f"(d[7]),"+f"(d[8]),"+f"(d[9]),"+f"(d[10]),"+f"(d[11]),"+f"(d[12]),"+f"(d[13]),"+f"(d[14]),"+f"(d[15]),"+f"(d[16]),"+f"(d[17]),"+f"(d[18]),"+f"(d[19]),"+f"(d[20]),"+f"(d[21]),"+f"(d[22]),"+f"(d[23]),"+f"(d[24]),"+f"(d[25]),"+f"(d[26]),"+f"(d[27]),"+f"(d[28]),"+f"(d[29]),"+f"(d[30]),"+f"(d[31]),"+f"(d[32]),"+f"(d[33]),"+f"(d[34]),"+f"(d[35]),"+f"(d[36]),"+f"(d[37]),"+f"(d[38]),"+f"(d[39]),"+f"(d[40]),"+f"(d[41]),"+f"(d[42]),"+f"(d[43]),"+f"(d[44]),"+f"(d[45]),"+f"(d[46]),"+f"(d[47]),"+f"(d[48]),"+f"(d[49]),"+f"(d[50]),"+f"(d[51]),"+f"(d[52]),"+f"(d[53]),"+f"(d[54]),"+f"(d[55]),"+f"(d[56]),"+f"(d[57]),"+f"(d[58]),"+f"(d[59]),"+f"(d[60]),"+f"(d[61]),"+f"(d[62]),"+f"(d[63])
    : "r"(da), "r"(oa), "r"(db), "r"(ob), "r"(sd), "n"(TB));
}
template <int TB> __device__ __forceinline__ void wgmma_rs_n64(float (&d)[32], const uint32_t* a, uint32_t db, int ob, int sd) {
  asm volatile("{\n.reg .pred p;\n.reg .b32 t;\n.reg .b64 b;\nsetp.ne.b32 p, %38, 0;\nadd.u32 t, %36, %37;\nmov.b64 b, {t, 0x40000040};\n"
    "wgmma.mma_async.sync.aligned.m64n64k16.f32.bf16.bf16 {%0,%1,%2,%3,%4,%5,%6,%7,%8,%9,%10,%11,%12,%13,%14,%15,%16,%17,%18,%19,%20,%21,%22,%23,%24,%25,%26,%27,%28,%29,%30,%31}, "
    "{%32,%33,%34,%35}, b, p, 1, 1, %39;\n}"
    : "+f"(d[0]),"+f"(d[1]),"+f"(d[2]),"+f"(d[3]),"+f"(d[4]),"+f"(d[5]),"+f"(d[6]),"+f"(d[7]),"+f"(d[8]),"+f"(d[9]),"+f"(d[10]),"+f"(d[11]),"+f"(d[12]),"+f"(d[13]),"+f"(d[14]),"+f"(d[15]),"+f"(d[16]),"+f"(d[17]),"+f"(d[18]),"+f"(d[19]),"+f"(d[20]),"+f"(d[21]),"+f"(d[22]),"+f"(d[23]),"+f"(d[24]),"+f"(d[25]),"+f"(d[26]),"+f"(d[27]),"+f"(d[28]),"+f"(d[29]),"+f"(d[30]),"+f"(d[31])
    : "r"(a[0]), "r"(a[1]), "r"(a[2]), "r"(a[3]), "r"(db), "r"(ob), "r"(sd), "n"(TB));
}
template <int TB> __device__ __forceinline__ void wgmma_ss_n64(float (&d)[32], uint32_t da, int oa, uint32_t db, int ob, int sd) {
  asm volatile("{\n.reg .pred p;\n.reg .b32 t, u;\n.reg .b64 a, b;\nsetp.ne.b32 p, %36, 0;\nadd.u32 u, %32, %33;\nmov.b64 a, {u, 0x40000040};\nadd.u32 t, %34, %35;\nmov.b64 b, {t, 0x40000040};\n"
    "wgmma.mma_async.sync.aligned.m64n64k16.f32.bf16.bf16 {%0,%1,%2,%3,%4,%5,%6,%7,%8,%9,%10,%11,%12,%13,%14,%15,%16,%17,%18,%19,%20,%21,%22,%23,%24,%25,%26,%27,%28,%29,%30,%31}, "
    "a, b, p, 1, 1, 0, %37;\n}"
    : "+f"(d[0]),"+f"(d[1]),"+f"(d[2]),"+f"(d[3]),"+f"(d[4]),"+f"(d[5]),"+f"(d[6]),"+f"(d[7]),"+f"(d[8]),"+f"(d[9]),"+f"(d[10]),"+f"(d[11]),"+f"(d[12]),"+f"(d[13]),"+f"(d[14]),"+f"(d[15]),"+f"(d[16]),"+f"(d[17]),"+f"(d[18]),"+f"(d[19]),"+f"(d[20]),"+f"(d[21]),"+f"(d[22]),"+f"(d[23]),"+f"(d[24]),"+f"(d[25]),"+f"(d[26]),"+f"(d[27]),"+f"(d[28]),"+f"(d[29]),"+f"(d[30]),"+f"(d[31])
    : "r"(da), "r"(oa), "r"(db), "r"(ob), "r"(sd), "n"(TB));
}

struct RowStat {
  uint32_t m2, rh, rl;
  __device__ __forceinline__ uint32_t norm_half(uint32_t x) const { uint32_t d = hsub2(x, m2); return hfma2(d, rh, hmul2(d, rl)); }
  __device__ __forceinline__ void resid(float& a, float& b, uint32_t x, uint32_t d2) const {
    uint32_t t = hmul2(norm_half(x), d2);
    a = bf_lo(x) + bf_lo(t); b = bf_hi(x) + bf_hi(t);
  }
};
__device__ __forceinline__ RowStat row_stat(uint2 s) { return RowStat{__byte_perm(s.x, 0, 0x1010), __byte_perm(s.x, 0, 0x3232), __byte_perm(s.y, 0, 0x1010)}; }
__device__ __forceinline__ void load_row(uint2 (&v)[9], const Params& p, int row, int lane) {
  const uint2* xp = reinterpret_cast<const uint2*>(p.xg + (size_t)row * DM) + (lane & 15);
#pragma unroll
  for (int i = 0; i < 9; i++) asm volatile("ld.global.nc.v2.b32 {%0,%1}, [%2];" : "=r"(v[i].x), "=r"(v[i].y) : "l"(xp + 16 * i));
}
__device__ __forceinline__ void publish_stats(const uint2 (&v)[2][9], int row, int lane) {
  float s[2] = {}, q[2] = {};
#pragma unroll
  for (int i = 0; i < 18; i++) { const uint2 a = v[i & 1][i >> 1]; s[i & 1] += (bf_lo(a.x) + bf_hi(a.x)) + (bf_lo(a.y) + bf_hi(a.y)); }
#pragma unroll
  for (int o = 1; o < 16; o <<= 1) { s[0] += __shfl_xor_sync(~0u, s[0], o); s[1] += __shfl_xor_sync(~0u, s[1], o); }
  s[0] *= 1.f / DM; s[1] *= 1.f / DM;
#pragma unroll
  for (int i = 0; i < 18; i++) {
    const uint2 w = v[i & 1][i >> 1];
    const float mean = s[i & 1], a = bf_lo(w.x) - mean, b = bf_hi(w.x) - mean, c = bf_lo(w.y) - mean, d = bf_hi(w.y) - mean;
    q[i & 1] += fmaf(a, a, b * b) + fmaf(c, c, d * d);
  }
#pragma unroll
  for (int o = 1; o < 16; o <<= 1) { q[0] += __shfl_xor_sync(~0u, q[0], o); q[1] += __shfl_xor_sync(~0u, q[1], o); }
  const bool second = lane & 1;
  const float r = __fdividef(0.5f, bf_round(__fsqrt_rn(bf_round(bf_round((second ? q[1] : q[0]) * (1.f / DM)) + 1e-5f)))), rhi = bf_round(r);
  bar_sync(6, 160);
  const uint32_t par = get_par();
  if ((lane & 15) < 2) st_tag8(g_stats + row + 2 * second, pack2(second ? s[1] : s[0], rhi), (pack2(r - rhi, 0.f) & 0xffffu) | (par << 16));
}
__device__ __forceinline__ void get_stats(float& r0, float& r1, uint32_t& m0, uint32_t& m1, const uint2* sp, uint2 s0, uint2 s1, int w8, int lane) {
  const int row = w8 * 16 + (lane >> 2);
  const uint32_t par = get_par();
  while (__any_sync(~0u, ((s0.y >> 16) != par) | ((s1.y >> 16) != par))) { s0 = ld_tag8(sp); s1 = ld_tag8(sp + 8); }
  if ((lane & 3) == 0) { sts64(OFF_STATS + row * 8, s0.x, s0.y); sts64(OFF_STATS + row * 8 + 64, s1.x, s1.y); }
  r0 = bf_hi(s0.x) + bf_lo(s0.y); r1 = bf_hi(s1.x) + bf_lo(s1.y);
  m0 = __byte_perm(s0.x, 0, 0x1010); m1 = __byte_perm(s1.x, 0, 0x1010);
}
template <class F>
__device__ __forceinline__ uint32_t load_centered(uint32_t (&xa)[144], uint32_t fa, uint32_t bar, uint32_t xpar, uint32_t zero, bool own, const uint2* sp, F stats) {
  float s[4][4] = {};
  uint32_t dep = 0, a, b;
  uint2 s0 = {0, ~0u}, s1 = {0, ~0u};
#pragma unroll
  for (int g = 0; g < 3; g++) {
    mbar_wait(bar + g * 8, xpar);
    if (g == STG_AT && !own) { s0 = ld_tag8(sp); s1 = ld_tag8(sp + 8); }
#pragma unroll
    for (int i = 12 * g; i < 12 * g + 12; i++) ldsm4(&xa[4 * i], (fa ^ ((i & 3) << 5)) + (i >> 2) * UNIT);
    if (own) {
#pragma unroll
      for (int k = 12 * g; k < 12 * g + 12; k++)
        asm("mma.sync.aligned.m16n8k16.row.col.f32.bf16.bf16.f32 {%0,%1,%2,%3}, {%4,%5,%6,%7}, {%8,%8}, {%0,%1,%2,%3};"
            : "+f"(s[k & 3][0]), "+f"(s[k & 3][1]), "+f"(s[k & 3][2]), "+f"(s[k & 3][3])
            : "r"(xa[4 * k]), "r"(xa[4 * k + 1]), "r"(xa[4 * k + 2]), "r"(xa[4 * k + 3]), "r"(0x3F803F80u));
    }
#pragma unroll
    for (int k = 12 * g; k < 12 * g + 12; k++) dep |= xa[4 * k];
  }
  if (own) {
    const float m0 = ((s[0][0] + s[1][0]) + (s[2][0] + s[3][0])) * (1.f / DM), m1 = ((s[0][2] + s[1][2]) + (s[2][2] + s[3][2])) * (1.f / DM);
    a = pack2(m0, m0); b = pack2(m1, m1);
  } else {
    stats(a, b, s0, s1);
  }
#pragma unroll
  for (int i = 0; i < 144; i += 2) { xa[i] = hsub2(xa[i], a); xa[i + 1] = hsub2(xa[i + 1], b); }
  return dep & zero;
}

__device__ __forceinline__ uint32_t ring_get(uint32_t e, int tr) {
  TR(tr, 0);
  mbar_wait(BAR_FULL + (e & 15) * 8, (e >> 4) & 1);
  TR(tr, 1);
  return sb + (e & 15) * 2 * UNIT;
}
__device__ __forceinline__ void ring_put(uint32_t e, uint32_t dep = 0) { mbar_arrive_w(BAR_EMPTY + (e & 15) * 8 + dep); }

template <int TB, class F>
__device__ __forceinline__ void tile_rs(float (&acc)[64], const uint32_t (&xa)[144], const uint8_t* tab, int wg, int skew_bar, int s0, F shadow) {
  uint32_t prev = 0;
  if (wg == 1) bar_sync(skew_bar, 256);
#pragma unroll
  for (int kb = 0; kb < 9; kb++) {
    const uint32_t e = tab[kb], ba = ring_get(e, s0 + kb);
    const uint32_t db = TB ? desc_mn(ba) : desc_k(ba);
    wg_fence();
#pragma unroll
    for (int ks = 0; ks < 4; ks++) wgmma_rs_n128<TB>(acc, &xa[kb * 16 + ks * 4], db, TB ? ks * 128 : ks * 2, (kb | ks) != 0);
    wg_commit();
    if (kb == SKEW - 1 && wg == 0) bar_arrive(skew_bar, 256);
    if (kb == 8) shadow();
    if (kb > 0) { wg_wait<1>(); TR(s0 + kb - 1, 2); ring_put(prev); }
    prev = e;
  }
  wg_wait<0>();
  TR(s0 + 8, 2);
  ring_put(prev);
  fence_regs(acc);
}
__device__ __forceinline__ uint32_t glu2(const float (&acc)[64], int i, float r) {
  const float u0 = r * acc[32 + 2 * i], u1 = r * acc[33 + 2 * i];
  return pack2(fmaf(u0, tanh_hw(r * acc[2 * i]), u0), fmaf(u1, tanh_hw(r * acc[2 * i + 1]), u1));
}
__device__ __forceinline__ void stash_v(const float (&acc)[64], uint32_t wb, int warp, int lane, float r0, float r1) {
  const uint32_t b = wb + (warp * 16 + (lane >> 2)) * 256 + (lane & 3) * 8 + (lane & 12) * 8;
#pragma unroll
  for (int G = 0; G < 8; G++) {
    const uint32_t a = (b ^ ((G & 3) << 5)) + ((G & 4) << 5);
    sts64(a, pack2(r0 * acc[4 * G], r0 * acc[32 + 4 * G]), pack2(r0 * acc[4 * G + 1], r0 * acc[33 + 4 * G]));
    sts64(a + 8 * 256, pack2(r1 * acc[4 * G + 2], r1 * acc[34 + 4 * G]), pack2(r1 * acc[4 * G + 3], r1 * acc[35 + 4 * G]));
  }
}

__device__ __forceinline__ uint4* part_ptr(int m, int owner, int sender) { return g_part + (size_t)((m * 9 + owner) * 9 + sender) * 1024; }
template <int N>
__device__ __forceinline__ void pack_part(uint32_t* pk, const float (&a)[N], uint32_t par) {
#pragma unroll
  for (int i = 0; i < N / 2; i++) { pk[i] = pack2(a[2 * i], a[2 * i + 1]); if (!(i & 1)) pk[i] = (pk[i] & ~1u) | par; }
}
__device__ __forceinline__ void recv_issue(uint32_t* t, const uint4* src) {
#pragma unroll
  for (int i = 0; i < 4; i++) ld_tag16(&t[4 * i], src + i * 32);
}
__device__ __forceinline__ void recv_add(float (&R)[32], uint32_t* t, const uint4* src, uint32_t par) {
  while (__any_sync(~0u, ((t[0] ^ par) | (t[4] ^ par) | (t[8] ^ par) | (t[12] ^ par)) & 1)) recv_issue(t, src);
#pragma unroll
  for (int i = 0; i < 16; i++) { R[2 * i] += bf_lo(t[i]); R[2 * i + 1] += bf_hi(t[i]); }
}
__device__ __forceinline__ void init_resid(float (&R)[32], uint32_t xb, uint2 s0, uint2 s1, int lane) {
  const RowStat a = row_stat(s0), b = row_stat(s1);
#pragma unroll
  for (int ks = 0; ks < 4; ks++) {
    uint32_t x[4];
    ldsm4(x, xb ^ (ks << 5));
#pragma unroll
    for (int i = 0; i < 4; i++) ((i & 1) ? b : a).resid(R[8 * ks + 2 * i], R[8 * ks + 2 * i + 1], x[i], lds32(OFF_DSK + ks * 32 + (i >> 1) * 16 + (lane & 3) * 4));
  }
}
__device__ __forceinline__ void store_out(const float (&R)[32], float* o, int lane) {
  o += (lane & 1) * 8 + (lane & 2) * 2;
  const bool odd = lane & 1;
#pragma unroll
  for (int i = 0; i < 8; i++) {
    const int k = (i >> 1) * 8 + (i & 1) * 2;
    const float r0 = __shfl_xor_sync(~0u, odd ? R[k] : R[k + 4], 1), r1 = __shfl_xor_sync(~0u, odd ? R[k + 1] : R[k + 5], 1);
    __stcs(reinterpret_cast<float4*>(o + (i >> 1) * 16 + (i & 1) * 8 * DM), odd ? make_float4(r0, r1, R[k + 4], R[k + 5]) : make_float4(R[k], R[k + 1], r0, r1));
  }
}
__device__ __forceinline__ void mma_g8(float (&acc)[32], uint32_t are, uint32_t aim, uint32_t cb) {
  wg_fence();
#pragma unroll
  for (int ks = 0; ks < 4; ks++) wgmma_ss_n64<0>(acc, desc_k(are), ks * 2, desc_k(cb), ks * 2, ks != 0);
#pragma unroll
  for (int ks = 0; ks < 4; ks++) wgmma_ss_n64<0>(acc, desc_k(aim), ks * 2, desc_k(cb), 512 + ks * 2, 1);
  wg_commit();
}

__device__ __forceinline__ float2 cmad(float2 a, float2 b, float2 c) {
  return make_float2(fmaf(a.x, b.x, fmaf(-a.y, b.y, c.x)), fmaf(a.x, b.y, fmaf(a.y, b.x, c.y)));
}
__device__ __forceinline__ float2 csq(float2 a) { return make_float2(fmaf(a.x, a.x, -a.y * a.y), 2.f * a.x * a.y); }
__device__ __forceinline__ void ssm_coef(const Params& p, int ch, float2& lam, float2& coef) {
  float a = __bfloat162float(p.lam_re[ch]), b = __bfloat162float(p.lam_im[ch]);
  float dt = bf_round(expf(__bfloat162float(p.log_dt[ch])));
  float e = expf(dt * a), sn, cs;
  sincospif(dt * b * 0.318309886183790672f, &sn, &cs);
  lam.x = e * cs; lam.y = e * sn;
  float nr = lam.x - 1.f, inv = __fdividef(4.f, a * a + b * b);
  coef.x = (nr * a + lam.y * b) * inv; coef.y = (lam.y * a - nr * b) * inv;
}
template <int NSEG>
__device__ __forceinline__ void ssm_scan(float2 lam, float2 coef, int c, int seg, int grp, int m, uint32_t par, uint32_t zero) {
  constexpr int TPW = 128 / NSEG, LB = NSEG > 1 ? 8 : 4;
  const int tb = seg * TPW;
  float2 s = {0.f, 0.f};
  uint32_t v[8], sa0 = sb + (tb >> 6) * WREG + (tb & 63) * 256 + c * 4;
  asm volatile("" : "+r"(sa0));
  uint32_t sa = sa0;
#pragma unroll
  for (int u = 0; u < 8; u++) v[u] = lds32((sa ^ ((u & 3) << 5)) + u * 256);
#pragma unroll 1
  for (int i = 0; i < TPW / 8; i++) {
    sa += (NSEG == 1 && i == 7) ? WREG - 7 * 2048 : 2048;
#pragma unroll
    for (int u = 0; u < 8; u++) {
      s = cmad(lam, s, make_float2(bf_lo(v[u]), bf_hi(v[u])));
      v[u] = lds32((sa ^ ((u & 3) << 5)) + u * 256);
    }
  }
  if (NSEG == 1 && c == 0) PROBE(2, 3);
  float2 pw = lam;
#pragma unroll 1
  for (int k = 1; k < TPW; k <<= 1) pw = csq(pw);
  const uint32_t xch = sb + 9 * UNIT + c * 8;
  if (NSEG > 1) {
    sts64(xch + seg * 512, __float_as_uint(s.x), __float_as_uint(s.y));
    bar_sync(5, 256);
    if (seg == NSEG - 1) {
      s = make_float2(0.f, 0.f);
#pragma unroll 1
      for (int w = 0; w < NSEG; w++) s = cmad(pw, s, lds64f(xch + w * 512));
    }
  }
  uint2* st = g_state + grp * 16 * 64 + c;
  if (seg == NSEG - 1) st_tag8(st + m * 64, (__float_as_uint(s.x) & ~1u) | par, __float_as_uint(s.y));
  float2 pl = pw;
#pragma unroll 1
  for (int k = TPW; k < 128; k <<= 1) pl = csq(pl);
  s = make_float2(0.f, 0.f);
#pragma unroll 1
  for (int k = m; k > 0; k -= LB, st += LB * 64) {
    uint2 a[LB];
    uint32_t it = 0, bad;
    do {
      if (++it > (1u << 21)) __trap();
      bad = 0;
#pragma unroll
      for (int i = 0; i < LB; i++) { a[i].x = par; if (i < k) a[i] = ld_tag8(st + i * 64); }
#pragma unroll
      for (int i = 0; i < LB; i++) bad |= a[i].x ^ par;
    } while (__any_sync(~0u, bad & 1));
#pragma unroll
    for (int i = 0; i < LB; i++)
      if (i < k) s = cmad(pl, s, make_float2(__uint_as_float(a[i].x), __uint_as_float(a[i].y)));
  }
  if (NSEG > 1) {
#pragma unroll 1
    for (int w = 0; w < seg; w++) s = cmad(pw, s, lds64f(xch + w * 512));
  }
  if (NSEG == 1 && c == 0) PROBE(2, 4);
  sa = sa0;
  uint32_t* hg = reinterpret_cast<uint32_t*>(g_hs + (size_t)(m * 128 + tb) * 1152 + grp * 128) + ((sa0 & 255) >> 3) + (sa0 & 4) * 8;
  const uint32_t sel = (sa0 & 4) ? 0x3276 : 0x5410;
#pragma unroll
  for (int u = 0; u < 4; u++) v[u] = lds32((sa ^ (u << 5)) + u * 256);
#pragma unroll 1
  for (int i = 0; i < TPW / 4; i++) {
    sa += (NSEG == 1 && i == 15) ? WREG - 15 * 1024 : 1024;
    uint32_t y[4];
#pragma unroll
    for (int u = 0; u < 4; u++) {
      s = cmad(lam, s, make_float2(bf_lo(v[u]), bf_hi(v[u])));
      y[u] = pack2(fmaf(coef.x, s.x, -coef.y * s.y), fmaf(-coef.x, s.y, -coef.y * s.x));
      v[u] = __shfl_xor_sync(~0u, y[u], 1);
    }
#pragma unroll
    for (int u = 0; u < 4; u++) {
      hg[u * 576] = __byte_perm(y[u], v[u], sel);
      v[u] = lds32((sa ^ (u << 5)) + u * 256);
    }
    hg += 4 * 576;
  }
  if (NSEG > 1) mbar_arrive_w(BAR_P1 + (v[0] & v[1] & v[2] & v[3] & zero));
  fence_async_all();
  __syncwarp();
}

__host__ __device__ constexpr int kb_tile(int kk) { return kk < 4 ? kk : kk == 4 ? 8 : kk - 1; }
template <int N>
__device__ __forceinline__ void mma_block(float (&acc)[N / 2], const uint32_t (&hr)[80], int kk, uint32_t da, uint32_t ba, bool first) {
  const uint32_t db = kk >= 9 ? desc_k(ba) : desc_mn(ba);
  const int oa = (kk < 4 ? 7 - kk : kk - 9) * (UNIT >> 4);
#pragma unroll
  for (int ks = 0; ks < 4; ks++) {
    const int sd = !(first && ks == 0);
    if (kk >= 9) {
      if constexpr (N == 128) wgmma_ss_n128<0>(acc, da, oa + ks * 2, db, ks * 2, sd); else wgmma_ss_n64<0>(acc, da, oa + ks * 2, db, ks * 2, sd);
    } else if (kk < 4) {
      if constexpr (N == 128) wgmma_ss_n128<1>(acc, da, oa + ks * 2, db, ks * 128, sd); else wgmma_ss_n64<1>(acc, da, oa + ks * 2, db, ks * 128, sd);
    } else {
      if constexpr (N == 128) wgmma_rs_n128<1>(acc, &hr[(kk - 4) * 16 + ks * 4], db, ks * 128, sd);
      else wgmma_rs_n64<1>(acc, &hr[(kk - 4) * 16 + ks * 4], db, ks * 128, sd);
    }
  }
}

__device__ __forceinline__ void spare_scan(const Params& p, int m, int r, int w8, int lane) {
  const uint32_t par = get_par();
  float2 lam, coef;
  ssm_coef(p, 512 + (w8 & 1) * 32 + lane, lam, coef);
  CPROBE(6 + 4 * r);
  bar_sync(5, 256);
  mbar_arrive_w(BAR_STASH);
  ssm_scan<4>(lam, coef, (w8 & 1) * 32 + lane, w8 >> 1, 8, m, par, p.zero);
  mbar_arrive_w(BAR_SCAN);
  CPROBE(7 + 4 * r);
}
__device__ __forceinline__ void spare_atom8(const Params& p, const uint8_t* tab, int m, int wg, int w8, int lane) {
  float acc[32];
  const uint32_t are = ring_get(tab[0], 150), aim = ring_get(tab[1], 150), cb = ring_get(tab[2], 150);
  mma_g8(acc, are + wg * UNIT, aim + wg * UNIT, cb);
  wg_wait<0>();
  ring_put(tab[0]); ring_put(tab[1]); ring_put(tab[2]);
  fence_regs(acc);
  uint32_t pk[16];
  pack_part(pk, acc, get_par());
#pragma unroll
  for (int i = 0; i < 4; i++) st_tag16(part_ptr(m, 8, 8) + w8 * 128 + lane + i * 32, &pk[4 * i]);
  CPROBE(21 + (m >> 2));
}

__device__ __forceinline__ void consumer(const Params& p, bool spare, int m, int j, int wg, int warp, int lane) {
  const uint32_t wb = sb + wg * WREG;
  const uint32_t frag = (warp * 16 + (lane & 15)) * 128 + (((lane >> 4) ^ (lane & 7)) << 4);
  const int w8 = wg * 4 + warp;
  if (wg == 0) {
    bar_sync(0, 256);
  } else if (spare) {
    bar_sync(6, 160);
  } else {
    uint2 v[2][9];
    const int row = m * 128 + j * 16 + warp * 4 + (lane >> 4);
    load_row(v[0], p, row, lane); load_row(v[1], p, row + 2, lane);
    publish_stats(v, row, lane);
  }
  CPROBE(20);
  uint32_t hr[80];
  {
    uint32_t xa[144];
    float acc[64], r0, r1;
#pragma unroll 1
    for (int r = 0;; r++) {
      ring_put(6 - 5 * wg); ring_put(7 - 5 * wg); ring_put(9 - 5 * wg);
      const bool own = wg == 0 && r == 0;
      const uint2* sp = g_stats + (m + 4 * r) * 128 + w8 * 16 + (lane >> 2);
      const uint32_t dep = load_centered(xa, wb + frag, BAR_X + wg * 24, r & 1, p.zero, own, sp, [&](uint32_t& a, uint32_t& b, uint2 s0, uint2 s1) { get_stats(r0, r1, a, b, sp, s0, s1, w8, lane); });
      ring_put(1 + 5 * wg, dep); ring_put(2 + 5 * wg, dep); ring_put(4 + 5 * wg, dep);
      CPROBE(spare ? 5 + 4 * r : 1);
      tile_rs<0>(acc, xa, spare ? p.sched_sp + (r ? 12 * r - 3 : 0) : p.sched, wg, 2, 0, [&] { uint32_t a, b; if (own) get_stats(r0, r1, a, b, sp - 0, make_uint2(0, ~0u), make_uint2(0, ~0u), w8, lane); });
      stash_v(acc, wb, warp, lane, r0, r1);
      if (!spare) break;
      spare_scan(p, m + 4 * r, r, w8, lane);
#pragma unroll 1
      for (int q = r > 0 ? r - 1 : 1; q <= (r == 3 ? 3 : r - 1); q++) spare_atom8(p, p.sched_sp + 12 * q + (q < 3 ? 18 : 9), m + 4 * q, wg, w8, lane);
      if (r == 3) { mbar_arrive_w(BAR_DONE); return; }
    }
    __syncwarp();
    mbar_arrive_w(BAR_STASH);
    CPROBE(2);
#pragma unroll 1
    for (int t = 0;; t++) {
      tile_rs<1>(acc, xa, p.sched + 9 + 9 * t, wg, 1 + (t & 1), 9 + 9 * t, [&] {
        const uint32_t rc = p.reclaim[wg][t & 7];
        if (rc & 128) mbar_wait(BAR_EMPTY + (rc & 15) * 8, (rc >> 5) & 1);
        if (t == SCANT) {
          mbar_wait(BAR_SCAN, 0);
          fence_async();
          bar_sync(3 + wg, 128);
        }
      });
      if (t == 8) break;
      const uint32_t ha = wb + (7 - t) * UNIT + frag;
#pragma unroll
      for (int ks = 0; ks < 4; ks++) {
        uint32_t h[4];
#pragma unroll
        for (int i = 0; i < 4; i++) h[i] = glu2(acc, ks * 4 + i, (i & 1) ? r1 : r0);
        stsm4(ha ^ (ks << 5), h);
      }
      CPROBE(3 + t);
    }
    __syncwarp();
#pragma unroll
    for (int b = 0; b < 4; b++)
#pragma unroll
      for (int ks = 0; ks < 4; ks++) ldsm4(&hr[16 + b * 16 + ks * 4], wb + (3 - b) * UNIT + (frag ^ (ks << 5)));
#pragma unroll
    for (int i = 0; i < 16; i++) hr[i] = glu2(acc, i, (i & 1) ? r1 : r0);
  }
  {
    uint32_t dep = 0;
#pragma unroll
    for (int i = 16; i < 80; i += 4) dep |= hr[i];
    dep &= p.zero;
    ring_put(0, dep); ring_put(5, dep); ring_put(1, dep); ring_put(6, dep);
  }
  CPROBE(11);
  const uint32_t par = get_par();
  uint4* const pb = part_ptr(m, 0, 0) + w8 * 128 + lane;
  auto src = [&](int d) { return pb + (j * 9 + ((j - d) & 7)) * 1024; };
  auto dst = [&](int d) { return pb + ((d ? (j + d) & 7 : 8) * 9 + j) * 1024; };
  const uint8_t* tab = p.sched + 90;
  const uint32_t da = __shfl_sync(~0u, desc_k(wb), 0);
  float R[32];
  uint32_t pk[32];
#pragma unroll 1
  for (int ps = 0; ps < 4; ps++) {
    float acc[64];
    uint32_t prev = 0, prev2 = 0;
    if (wg == 1) bar_sync(2 - (ps & 1), 256);
#pragma unroll
    for (int kk = 0; kk < 11; kk++) {
      const uint32_t e = tab[kk], ba = ring_get(e, 90 + 11 * ps + kk);
      if (kk == 9 && ps == 0) mbar_wait(BAR_FULL + wg * 5 * 8, (p.sched[NSLOT + wg] >> 4) & 1);
      wg_fence();
      mma_block<128>(acc, hr, kk, da, ba, kk == 0);
      wg_commit();
      if (kk == SKEW2 - 1 && wg == 0) bar_arrive(2 - (ps & 1), 256);
      if (kk == XKK && ps == XPS) {
        const uint32_t ex = tab[XKK + 1], sa = OFF_STATS + (w8 * 16 + (lane >> 2)) * 8;
        init_resid(R, ring_get(ex, 151) + wg * UNIT + frag, lds64(sa), lds64(sa + 64), lane);
        ring_put(ex, (__float_as_uint(R[0]) | __float_as_uint(R[8]) | __float_as_uint(R[16]) | __float_as_uint(R[24])) & p.zero);
        tab++;
      }
      if (kk < 8 && ps > 0) st_tag16(dst(2 * ps - 2 + (kk >> 2)) + (kk & 3) * 32, &pk[kk * 4]);
      if (kk == 6 && ps == 1) mbar_arrive_w(BAR_P1);
      if (kk == 8 && ps > 1) { recv_issue(pk, src(2 * ps - 3)); if (ps > 2) recv_issue(pk + 16, src(2 * ps - 4)); }
      if (kk == 10 && ps > 1) { recv_add(R, pk, src(2 * ps - 3), par); if (ps > 2) recv_add(R, pk + 16, src(2 * ps - 4), par); }
      if (kk >= LAG2) { wg_wait<LAG2>(); TR(89 + 11 * ps + kk, 2); ring_put(LAG2 == 2 ? prev2 : prev); }
      prev2 = prev; prev = e;
    }
    tab += 11;
    if (LAG2 == 2) { wg_wait<1>(); ring_put(prev2); }
    wg_wait<0>();
    TR(100 + 11 * ps, 2);
    ring_put(prev);
    fence_regs(acc);
    pack_part(pk, acc, par);
    CPROBE(12 + ps);
  }
  {
    float acc[32];
    uint32_t t[16];
    recv_issue(t, src(4));
    if (wg == 1) bar_sync(2, 256);
    {
      const uint32_t are = ring_get(tab[0], 134), aim = ring_get(tab[1], 135), cb = ring_get(tab[2], 136);
      mma_g8(acc, are + wg * UNIT, aim + wg * UNIT, cb);
      tab += 3;
    }
#pragma unroll
    for (int s = 0; s < 6; s++) {
      if (s >= P5A && s < P5A + 8 / P5S) {
#pragma unroll
        for (int i = (s - P5A) * P5S; i < (s - P5A + 1) * P5S; i++) st_tag16(dst(6 + (i >> 2)) + (i & 3) * 32, &pk[i * 4]);
      }
      const uint32_t ba = ring_get(tab[s], 137 + s);
      wg_fence();
      mma_block<64>(acc, hr, 2 * s, da, ba, false);
      if (s < 5) mma_block<64>(acc, hr, 2 * s + 1, da, ba + UNIT, false);
      wg_commit();
      if (s == SKEW5 - 1 && wg == 0) bar_arrive(2, 256);
      if (s == 0) { wg_wait<1>(); ring_put(tab[-3]); }
      if (s == 1) { recv_add(R, t, src(4), par); recv_issue(t, src(5)); }
      if (s == 3) recv_add(R, t, src(5), par);
      if (s == P5R) { recv_issue(t, src(6)); recv_issue(pk, src(7)); }
    }
    CPROBE(28);
    recv_add(R, t, src(6), par); recv_add(R, pk, src(7), par);
    CPROBE(29);
    wg_wait<0>();
    TR(142, 2);
    fence_regs(acc);
    CPROBE(16);
#pragma unroll
    for (int i = 0; i < 32; i++) R[i] += acc[i];
    store_out(R, p.out + (size_t)(m * 128 + w8 * 16 + (lane >> 2)) * DM + j * 64, lane);
    mbar_arrive_w(BAR_DONE);
    CPROBE(17);
    TR(143, 0);
  }
}

__device__ __forceinline__ void load_x(const Params& p, int m, int wg, int g0, int g1) {
#pragma unroll 1
  for (int g = g0; g < g1; g++) {
    mbar_expect_tx(BAR_X + (wg * 3 + g) * 8, 3 * UNIT);
    tma_load3(sb + wg * WREG + g * 3 * UNIT, &p.x, 0, m * 128 + wg * 64, g * 3, BAR_X + (wg * 3 + g) * 8);
  }
}
__device__ __forceinline__ uint32_t slot_acquire(uint32_t e, uint32_t bytes) {
  const uint32_t bar = BAR_FULL + (e & 15) * 8;
  if (!(e & 64)) mbar_wait_b(bar + (BAR_EMPTY - BAR_FULL), (e >> 5) & 1);
  mbar_expect_tx(bar, bytes);
  return bar;
}
__device__ __forceinline__ void load_slot(uint32_t e, const CUtensorMap* m0, int a0, int b0, const CUtensorMap* m1, int a1, int b1) {
  uint32_t dst = sb + (e & 15) * 2 * UNIT;
  asm volatile("" : "+r"(dst), "+r"(a0), "+r"(b0), "+r"(a1), "+r"(b1));
  const uint32_t bar = slot_acquire(e, m1 ? 2 * UNIT : UNIT);
  tma_load(dst, m0, a0, b0, bar);
  if (m1) tma_load(dst + UNIT, m1, a1, b1, bar);
}
__device__ __forceinline__ const CUtensorMap* p2_box(const Params& p, int j, int kk, int a, int& c0, int& c1) {
  if (kk >= 9) { c0 = 64 * j; c1 = 64 * a; return kk == 9 ? &p.cre : &p.cim; }
  c0 = 64 * a; c1 = DM * j + 64 * kb_tile(kk);
  return &p.wd;
}
__device__ __forceinline__ void load_g8(const Params& p, const uint8_t* tab, int m, int a) {
#pragma unroll 1
  for (int k = 0; k < 2; k++) load_slot(tab[k], &p.hs, 1024 + 64 * k, m * 128, &p.hs, 1024 + 64 * k, m * 128 + 64);
  load_slot(tab[2], &p.cre, 512, 64 * a, &p.cim, 512, 64 * a);
}
__device__ __forceinline__ void producer_main(const Params& p, int m, int j) {
  const uint8_t* tab = p.sched;
#pragma unroll 1
  for (int kb = 0; kb < 9; kb++) {
    load_slot(*tab++, &p.bre, 64 * kb, 64 * j, &p.bim, 64 * kb, 64 * j);
    if (kb == 0 && XPRI >= 0) mbar_wait_b(BAR_X + XPRI * 8, 0);
    if (kb >= XAT && kb < XAT + 3) load_x(p, m, 1, kb - XAT, kb - XAT + 1);
  }
  PROBE(3, 2);
#pragma unroll 1
  for (int c = DM * j; c < DM * j + DM; c += 64)
#pragma unroll 1
    for (int k = 0; k < DM; k += 64) load_slot(*tab++, &p.wg, c, k, &p.wu, c, k);
  mbar_wait_b(BAR_SCAN, 0);
  tma_prefetch(&p.x2, 64 * j, m * 128);
#pragma unroll 1
  for (int k = 0; k < 4; k++) tma_prefetch(&p.hs, 128 * j + 64 * (k & 1), m * 128 + 32 * (k & 2));
#pragma unroll 1
  for (int ps = 0; ps < 4; ps++)
#pragma unroll 1
    for (int kk = 0; kk < 11; kk++) {
      int a0, b0, a1, b1;
      const CUtensorMap* mp = p2_box(p, j, kk, ps == 0 ? 8 : (j + 2 * ps) & 7, a0, b0);
      p2_box(p, j, kk, (j + 2 * ps + 1) & 7, a1, b1);
      load_slot(*tab++, mp, a0, b0, mp, a1, b1);
      if (kk == XKK && ps == XPS) {
        const uint32_t e = *tab++, bar = slot_acquire(e, 2 * UNIT);
        tma_load(sb + (e & 15) * 2 * UNIT, &p.x2, 64 * j, m * 128, bar);
      }
      if ((kk == SK0 || kk == SK1) && ps == 0) {
#pragma unroll 1
        for (int w = (kk != SK0); w <= (kk == SK1); w++) load_slot(p.sched[NSLOT + w], &p.hs, 128 * j, m * 128 + w * 64, &p.hs, 128 * j + 64, m * 128 + w * 64);
      }
    }
  mbar_wait_b(BAR_G8, 0);
  load_g8(p, tab, m, j);
  tab += 3;
#pragma unroll 1
  for (int s = 0; s < 6; s++) {
    int a0, b0, a1 = 0, b1 = 0;
    const CUtensorMap* m0 = p2_box(p, j, 2 * s, j, a0, b0);
    const CUtensorMap* m1 = s < 5 ? p2_box(p, j, 2 * s + 1, j, a1, b1) : nullptr;
    load_slot(*tab++, m0, a0, b0, m1, a1, b1);
  }
}
__device__ __forceinline__ void producer_spare(const Params& p, int s) {
  const uint8_t* tab = p.sched_sp;
  load_x(p, s, 1, 0, 3);
#pragma unroll 1
  for (int m = s; m < 16; m += 4) {
#pragma unroll 1
    for (int kb = 0; kb < 9; kb++) load_slot(*tab++, &p.bre, 64 * kb, 512, &p.bim, 64 * kb, 512);
    mbar_wait_b(BAR_STASH, (m >> 2) & 1);
    if (m < 12) { load_x(p, m + 4, 0, 1, 3); load_x(p, m + 4, 1, 1, 3); }
    if (m >= 4) { load_g8(p, tab, m - 4, 8); tab += 3; }
    mbar_wait_b(BAR_P1, (m >> 2) & 1);
    if (m < 12) { load_x(p, m + 4, 0, 0, 1); load_x(p, m + 4, 1, 0, 1); }
    mbar_wait_b(BAR_SCAN, (m >> 2) & 1);
  }
  load_g8(p, tab, s + 12, 8);
}

__device__ __forceinline__ void scan_worker(const Params& p, int m, int j, int c) {
  float2 lam, coef;
  ssm_coef(p, 64 * j + c, lam, coef);
  mbar_wait_b(BAR_STASH, 0);
  if (c == 0) PROBE(2, 1);
  ssm_scan<1>(lam, coef, c, 0, j, m, get_par(), 0);
  mbar_arrive_w(BAR_SCAN);
  if (c == 0) PROBE(2, 2);
}
__device__ __forceinline__ void reduce_atom8(const Params& p, int m, int j, int w, int lane) {
  mbar_wait_slow(BAR_P1, 0);
  const uint32_t par = get_par();
#pragma unroll 1
  for (int c = w; c < 8; c += 3) {
    const uint2* src = reinterpret_cast<const uint2*>(part_ptr(m, 8, 0) + j * 128 + (c >> 1) * 32 + lane) + (c & 1);
    float v[4] = {0.f, 0.f, 0.f, 0.f};
    uint2 a[5];
#pragma unroll 1
    for (int k = 0; k < 2; k++, src += 5 * 2048) {
      uint32_t it = 0;
      if (k) {
        const uint32_t* xp = reinterpret_cast<const uint32_t*>(p.xg + (size_t)(m * 128 + j * 16 + (lane >> 2)) * DM + 512 + 8 * c) + (lane & 3);
        a[4].x = xp[0]; a[4].y = xp[4 * DM];
      }
      while (true) {
#pragma unroll
        for (int i = 0; i < 4; i++) a[i] = ld_tag8(src + i * 2048);
        if (!k) a[4] = ld_tag8(src + 4 * 2048);
        if (!__any_sync(~0u, ((a[0].x ^ par) | (a[1].x ^ par) | (a[2].x ^ par) | (a[3].x ^ par) | (k ? 0 : a[4].x ^ par)) & 1)) break;
        if (++it > (1u << 21)) __trap();
        __nanosleep(400);
      }
#pragma unroll
      for (int i = 0; i < 5; i++)
        if (i < 4 || !k) { v[0] += bf_lo(a[i].x); v[1] += bf_hi(a[i].x); v[2] += bf_lo(a[i].y); v[3] += bf_hi(a[i].y); }
    }
    const int row = j * 16 + (lane >> 2);
    const uint32_t d2 = lds32(OFF_DSK + 128 + c * 16 + (lane & 3) * 4);
    float* o = p.out + (size_t)(m * 128 + row) * DM + 512 + 8 * c + 2 * (lane & 3);
#pragma unroll
    for (int h = 0; h < 2; h++) {
      float x0, x1;
      row_stat(lds64(OFF_STATS + (row + 8 * h) * 8)).resid(x0, x1, h ? a[4].y : a[4].x, d2);
      __stcs(reinterpret_cast<float2*>(o + h * 8 * DM), make_float2(v[2 * h] + x0, v[2 * h + 1] + x1));
    }
  }
  if (w == 0 && lane == 0) PROBE(2, 5);
}
__device__ __forceinline__ void prefetch_weights(const Params& p, int m, int j) {
  mbar_wait_b(BAR_X + PF_BAR * 8, 0);
#pragma unroll 1
  for (int n = m; n < 162; n += 16) {
    tma_prefetch((n & 1) ? &p.wu : &p.wg, DM * j + 64 * (n / 18), 64 * ((n % 18) >> 1));
    __nanosleep(PF_NS);
  }
#pragma unroll 1
  for (int n = m; n < 101; n += 16) {
    const int a = n / 11;
    int c0, c1;
    const CUtensorMap* mp = p2_box(p, n < 99 ? j : 8, n < 99 ? n % 11 : n - 90, n >= 99 ? j : a ? (j + a) & 7 : 8, c0, c1);
    tma_prefetch(mp, c0, c1);
    __nanosleep(PF_NS2);
  }
}

__global__ void __launch_bounds__(NTHREADS, 1) fused_kernel(const __grid_constant__ Params p) {
  extern __shared__ __align__(1024) uint8_t smem[];
  const int tid = threadIdx.x, b = blockIdx.x, lane = tid & 31;
  const bool spare = b >= 128;
  const int m = spare ? b - 128 : b >> 3, j = b & 7;
  if (tid < 256) {
    asm volatile("setmaxnreg.inc.sync.aligned.u32 240;");
    CPROBE(0);
    TR(145, 0);
    consumer(p, spare, m, j, tid >> 7, (tid >> 5) & 3, lane);
  } else {
    asm volatile("setmaxnreg.dec.sync.aligned.u32 24;");
    if (tid == 256) {
      PROBE(3, 0);
#pragma unroll
      for (int i = 0; i < 6; i++) mbar_init(BAR_X + i * 8, 1);
      fence_init();
      load_x(p, m, 0, 0, 3);
      PROBE(3, 4);
    } else if (tid == 288) {
#pragma unroll
      for (int i = 0; i < 14; i++) mbar_init(BAR_FULL + i * 8, 1);
      fence_init();
    } else if (tid == 320) {
#pragma unroll
      for (int i = 0; i < 14; i++) mbar_init(BAR_EMPTY + i * 8, 8);
      fence_init();
    } else if (tid == 352) {
      if ((uint32_t)__cvta_generic_to_shared(smem) != sb) __trap();
      mbar_init(BAR_STASH, 8); mbar_init(BAR_P1, 8); mbar_init(BAR_SCAN, spare ? 8 : 2); mbar_init(BAR_G8, 1); mbar_init(BAR_PAR, 1); mbar_init(BAR_DONE, 8);
      fence_init();
    }
    bar_sync(0, 256);
    if (tid >= 320 && tid < 352) bar_arrive(6, 160);
    if (tid < 288) {
      if (lane == 0) { PROBE(3, 3); if (!spare) producer_main(p, b >> 3, j); else producer_spare(p, b & 3); }
    } else if (tid < 352) {
      if (!spare) {
        scan_worker(p, b >> 3, j, tid - 288);
        reduce_atom8(p, b >> 3, j, (tid - 288) >> 5, lane);
      } else if (tid == 288) {
#pragma unroll 1
        for (int r = 0; r < 4; r++) {
          mbar_wait_b(BAR_SCAN, r & 1);
          asm volatile("st.release.gpu.global.b32 [%0], %1;" ::"l"(g_flag + (b & 3) + 4 * r), "r"(get_par()) : "memory");
        }
      }
    } else {
      const uint32_t ep = g_epoch[b] + 1;
      const uint32_t d = reinterpret_cast<const uint32_t*>(p.dskip)[32 * j + lane], d8 = reinterpret_cast<const uint32_t*>(p.dskip)[256 + lane];
      if (lane == 0 && b < 80) tma_prefetch((b & 8) ? &p.bim : &p.bre, 64 * (4 + (b >> 4)), 64 * j);
      if (lane < 10) asm volatile("prefetch.tensormap [%0];" ::"l"(&p.x + lane) : "memory");
      if (lane == 0) sts32(OFF_PAR, ep & 1);
      sts32(OFF_DSK + lane * 4, hadd2(d, d)); sts32(OFF_DSK + 128 + lane * 4, hadd2(d8, d8));
      __syncwarp();
      if (lane == 0) {
        mbar_arrive(BAR_PAR);
        g_epoch[b] = ep;
        if (!spare) {
          prefetch_weights(p, b >> 3, j);
          mbar_wait_slow(FLAGBAR, 0);
          uint32_t f, it = 0;
          while (true) {
            asm volatile("ld.acquire.gpu.global.b32 %0, [%1];" : "=r"(f) : "l"(g_flag + (b >> 3)) : "memory");
            if (f == (ep & 1)) break;
            if (++it > (1u << 21)) __trap();
            __nanosleep(300);
          }
          fence_async_all();
          mbar_arrive(BAR_G8);

        }
      }
      __syncwarp();
      if (!spare) reduce_atom8(p, b >> 3, j, 2, lane);
      if (lane == 0) mbar_wait_b(BAR_DONE, 0);
      __syncwarp();
      PROF_DUMP();
    }
  }
}

typedef CUresult (*EncodeFn)(CUtensorMap*, CUtensorMapDataType, cuuint32_t, void*, const cuuint64_t*, const cuuint64_t*, const cuuint32_t*,
                             const cuuint32_t*, CUtensorMapInterleave, CUtensorMapSwizzle, CUtensorMapL2promotion, CUtensorMapFloatOOBfill);

void make_map(EncodeFn fn, CUtensorMap* map, const void* ptr, int rows, int cols, int box_rows = 64, int kblocks = 0) {
  cuuint64_t dims[3] = {(cuuint64_t)(kblocks ? 64 : cols), (cuuint64_t)rows, (cuuint64_t)(cols / 64)}, strides[2] = {(cuuint64_t)cols * 2, 128};
  cuuint32_t box[3] = {64, (cuuint32_t)box_rows, (cuuint32_t)kblocks}, es[3] = {1, 1, 1};
  fn(map, CU_TENSOR_MAP_DATA_TYPE_BFLOAT16, kblocks ? 3 : 2, const_cast<void*>(ptr), dims, strides, box, es, CU_TENSOR_MAP_INTERLEAVE_NONE,
     CU_TENSOR_MAP_SWIZZLE_128B, CU_TENSOR_MAP_L2_PROMOTION_L2_128B, CU_TENSOR_MAP_FLOAT_OOB_FILL_NONE);
}

struct Win { int pair, from, until; };
struct RingSim {
  int rel[14] = {0}, uses[14] = {0}, last[14];
  RingSim() { for (int i = 0; i < 14; i++) last[i] = -100 + i; }
  uint8_t take(int pr, int i) {
    const int n = rel[pr];
    const uint8_t e = (uint8_t)(pr | ((uses[pr] & 1) << 4) | (n == 0 ? 64 : (((n - 1) & 1) << 5)));
    uses[pr]++; rel[pr]++; last[pr] = i;
    return e;
  }
  uint8_t next(const Win* win, int nwin, int i) {
    int best = -1;
    for (int w = 0; w < nwin; w++) {
      if (i == win[w].from && win[w].pair < 10) rel[win[w].pair]++;
      if (i >= win[w].from && i <= win[w].until && (best < 0 || last[win[w].pair] < last[best])) best = win[w].pair;
    }
    return take(best, i);
  }
};
void make_schedule(Params& p) {
  const Win win[] = {
    {10, 0, 999}, {11, 0, 999}, {12, 0, 999}, {13, 0, 999}, {4, 4, 999}, {9, 7, 999},
    {2, 4, EXT1_UNTIL}, {7, 7, EXT1_UNTIL},
    {1, RG2, 999}, {6, RG2, 999},
    {1, 4, EXT2_UNTIL}, {6, 7, EXT2_UNTIL},
  };
  RingSim r;
  for (int i = 0; i < NSLOT; i++) {
    p.sched[i] = r.next(win, sizeof(win) / sizeof(win[0]), i);
    if (i >= 17 && i < 89 && (i - 17) % 9 == 0)
      for (int w = 0, t = (i - 17) / 9; w < 2; w++) {
        const int pr = w * 5 + (7 - t) / 2;
        p.reclaim[w][t] = r.uses[pr] > 0 ? (uint8_t)(128 | pr | (((r.rel[pr] - 1) & 1) << 5)) : 0;
      }
  }
  for (int w = 0; w < 2; w++) { r.rel[5 * w]++; p.sched[NSLOT + w] = r.take(5 * w, NSLOT); }
  Win ws[28] = {{10, 0, 999}, {11, 0, 999}, {12, 0, 999}, {13, 0, 999}};
  for (int k = 0; k < 24; k++) ws[4 + k] = Win{(k & 1) * 5 + (k % 6 < 2 ? 1 : k % 6 < 4 ? 2 : 4), (k < 6 ? 4 : 12 * (k / 6) + 1), (k < 6 ? 8 : 12 * (k / 6) + 5)};
  RingSim q;
  for (int i = 0; i < NSLOT_SP; i++) p.sched_sp[i] = q.next(ws, 28, i);
}

}

extern "C" void kernel_launch(void* const* d_in, const int* in_sizes, int n_in, void* d_out, int out_size) {
  static EncodeFn fn = nullptr;
  static void* hs = nullptr;
  if (!fn) {
    void* f = nullptr;
    cudaDriverEntryPointQueryResult qr;
    cudaGetDriverEntryPoint("cuTensorMapEncodeTiled", &f, cudaEnableDefault, &qr);
    fn = (EncodeFn)f;
    cudaGetSymbolAddress(&hs, g_hs);
    cudaFuncSetAttribute(fused_kernel, cudaFuncAttributeMaxDynamicSharedMemorySize, SMEM_BYTES);
  }
  Params p;
  make_map(fn, &p.x, d_in[0], SEQ, DM, 64, 3);
  make_map(fn, &p.x2, d_in[0], SEQ, DM, 128);
  make_map(fn, &p.bre, d_in[3], DM, DM);
  make_map(fn, &p.bim, d_in[4], DM, DM);
  make_map(fn, &p.cre, d_in[5], DM, DM);
  make_map(fn, &p.cim, d_in[6], DM, DM);
  make_map(fn, &p.wg, d_in[10], DM, FF);
  make_map(fn, &p.wu, d_in[11], DM, FF);
  make_map(fn, &p.wd, d_in[12], FF, DM);
  make_map(fn, &p.hs, hs, SEQ, 1152);
  p.xg = (const __nv_bfloat16*)d_in[0];
  p.lam_re = (const __nv_bfloat16*)d_in[1];
  p.lam_im = (const __nv_bfloat16*)d_in[2];
  p.log_dt = (const __nv_bfloat16*)d_in[7];
  p.dskip = (const __nv_bfloat16*)d_in[8];
  p.out = (float*)d_out;
  p.zero = 0;
  make_schedule(p);
  fused_kernel<<<132, NTHREADS, SMEM_BYTES>>>(p);
}
```

```cpp
#include <cuda_runtime.h>
#include <cuda_bf16.h>
#include <cuda.h>
#include <stdint.h>

namespace {

constexpr int SEQ = 2048, DM = 576, FF = 4608;
constexpr uint32_t UNIT = 8192, WREG = 10 * UNIT;
constexpr int NSLOT = 144, NSLOT_SP = 48;
constexpr int SMEM_BYTES = 232448;
constexpr uint32_t sb = 1024;
constexpr uint32_t OFF_STATS = sb + 28 * UNIT;
constexpr uint32_t OFF_DSK = OFF_STATS + 1024;
constexpr uint32_t BAR_FULL = OFF_DSK + 256;
constexpr uint32_t BAR_EMPTY = BAR_FULL + 14 * 8;
constexpr uint32_t BAR_X = BAR_EMPTY + 14 * 8;
constexpr uint32_t BAR_STASH = BAR_X + 6 * 8;
constexpr uint32_t BAR_P1 = BAR_STASH + 8;
constexpr uint32_t BAR_SCAN = BAR_P1 + 8;
constexpr uint32_t BAR_G8 = BAR_SCAN + 8;
constexpr uint32_t BAR_PAR = BAR_G8 + 8;
constexpr uint32_t BAR_DONE = BAR_PAR + 8;
constexpr uint32_t OFF_PAR = BAR_DONE + 8;
constexpr int NTHREADS = 384;
constexpr int SKEW = 4, SKEW2 = 2;
constexpr int AHEAD = 3;

struct Params {
  CUtensorMap x, x2, wg, wu, wd, bre, bim, cre, cim, hs;
  const __nv_bfloat16 *xg, *lam_re, *lam_im, *log_dt, *dskip;
  float* out;
  uint32_t zero;
  uint32_t sched[NSLOT + 2];
  uint32_t sched_sp[NSLOT_SP];
  uint32_t reclaim[2][8];
};

__device__ uint4 g_part[16 * 9 * 9 * 1024];
__device__ uint2 g_state[9 * 16 * 64];
__device__ uint2 g_stats[SEQ];
__device__ __nv_bfloat16 g_hs[SEQ * 1152];
__device__ uint32_t g_flag[16];
__device__ uint32_t g_epoch[132];

__device__ __forceinline__ void mbar_init(uint32_t bar, uint32_t cnt) { asm volatile("mbarrier.init.shared::cta.b64 [%0], %1;" ::"r"(bar), "r"(cnt) : "memory"); }
__device__ __forceinline__ void mbar_expect_tx(uint32_t bar, uint32_t bytes) { asm volatile("{\n.reg .pred p;\nelect.sync _|p, 0xffffffff;\n@p mbarrier.arrive.expect_tx.shared::cta.b64 _, [%0], %1;\n}" ::"r"(bar), "r"(bytes) : "memory"); }
__device__ __forceinline__ void mbar_arrive(uint32_t bar) { asm volatile("mbarrier.arrive.shared::cta.b64 _, [%0];" ::"r"(bar) : "memory"); }
__device__ __forceinline__ void mbar_arrive_w(uint32_t bar) {
  asm volatile("{\n.reg .pred p;\nelect.sync _|p, 0xffffffff;\n@p mbarrier.arrive.shared::cta.b64 _, [%0];\n}" ::"r"(bar) : "memory");
}
__device__ __forceinline__ void mbar_wait(uint32_t bar, uint32_t parity) {
  asm volatile("{\n.reg .pred p;\nLOOP:\nmbarrier.try_wait.parity.shared::cta.b64 p, [%0], %1;\n@!p bra LOOP;\n}" ::"r"(bar), "r"(parity) : "memory");
}
__device__ __forceinline__ void mbar_wait_b(uint32_t bar, uint32_t parity) {
  asm volatile(
      "{\n.reg .pred p;\n.reg .u32 c;\nmov.u32 c, 0;\n"
      "LOOP:\nmbarrier.try_wait.parity.shared::cta.b64 p, [%0], %1;\n@p bra DONE;\n"
      "add.u32 c, c, 1;\nsetp.lt.u32 p, c, 0x400000;\n@p bra LOOP;\ntrap;\nDONE:\n}" ::"r"(bar), "r"(parity) : "memory");
}
__device__ __forceinline__ void mbar_wait_slow(uint32_t bar, uint32_t parity) {
  asm volatile(
      "{\n.reg .pred p;\n.reg .u32 c;\nmov.u32 c, 0;\n"
      "LOOP:\nmbarrier.test_wait.parity.shared::cta.b64 p, [%0], %1;\n@p bra DONE;\nnanosleep.u32 256;\n"
      "add.u32 c, c, 1;\nsetp.lt.u32 p, c, 0x400000;\n@p bra LOOP;\ntrap;\nDONE:\n}" ::"r"(bar), "r"(parity) : "memory");
}
__device__ __forceinline__ void tma_load(uint32_t dst, const CUtensorMap* map, int c0, int c1, uint32_t bar) {
  asm volatile("{\n.reg .pred p;\nelect.sync _|p, 0xffffffff;\n"
               "@p cp.async.bulk.tensor.2d.shared::cluster.global.mbarrier::complete_tx::bytes [%0], [%1, {%3, %4}], [%2];\n}"
               ::"r"(dst), "l"(map), "r"(bar), "r"(c0), "r"(c1) : "memory");
}
__device__ __forceinline__ void tma_load3(uint32_t dst, const CUtensorMap* map, int c0, int c1, int c2, uint32_t bar) {
  asm volatile("{\n.reg .pred p;\nelect.sync _|p, 0xffffffff;\n"
               "@p cp.async.bulk.tensor.3d.shared::cluster.global.mbarrier::complete_tx::bytes [%0], [%1, {%3, %4, %5}], [%2];\n}"
               ::"r"(dst), "l"(map), "r"(bar), "r"(c0), "r"(c1), "r"(c2) : "memory");
}
__device__ __forceinline__ void tma_prefetch(const CUtensorMap* map, int c0, int c1) {
  asm volatile("{\n.reg .pred p;\nelect.sync _|p, 0xffffffff;\n@p cp.async.bulk.prefetch.tensor.2d.L2.global [%0, {%1, %2}];\n}" ::"l"(map), "r"(c0), "r"(c1) : "memory");
}
__device__ __forceinline__ void fence_async() { asm volatile("fence.proxy.async.shared::cta;" ::: "memory"); }
__device__ __forceinline__ void fence_init() { asm volatile("fence.mbarrier_init.release.cluster;" ::: "memory"); }
__device__ __forceinline__ void fence_async_all() { asm volatile("fence.proxy.async;" ::: "memory"); }
__device__ __forceinline__ void bar_sync(int id, int n) { asm volatile("bar.sync %0, %1;" ::"r"(id), "r"(n) : "memory"); }
__device__ __forceinline__ void bar_arrive(int id, int n) { asm volatile("bar.arrive %0, %1;" ::"r"(id), "r"(n) : "memory"); }
__device__ __forceinline__ void wg_fence() { asm volatile("wgmma.fence.sync.aligned;" ::: "memory"); }
__device__ __forceinline__ void wg_commit() { asm volatile("wgmma.commit_group.sync.aligned;" ::: "memory"); }
template <int N> __device__ __forceinline__ void wg_wait() { asm volatile("wgmma.wait_group.sync.aligned %0;" ::"n"(N) : "memory"); }
template <int N> __device__ __forceinline__ void fence_regs(float (&a)[N]) {
#pragma unroll
  for (int i = 0; i < N; i++) asm volatile("" : "+f"(a[i])::"memory");
}
__device__ __forceinline__ void ldsm4(uint32_t* r, uint32_t addr) {
  asm volatile("ldmatrix.sync.aligned.m8n8.x4.shared.b16 {%0,%1,%2,%3}, [%4];" : "=r"(r[0]), "=r"(r[1]), "=r"(r[2]), "=r"(r[3]) : "r"(addr) : "memory");
}
__device__ __forceinline__ void stsm4(uint32_t addr, const uint32_t* r) {
  asm volatile("stmatrix.sync.aligned.m8n8.x4.shared.b16 [%0], {%1,%2,%3,%4};" ::"r"(addr), "r"(r[0]), "r"(r[1]), "r"(r[2]), "r"(r[3]) : "memory");
}
__device__ __forceinline__ void sts32(uint32_t addr, uint32_t a) { asm volatile("st.shared.b32 [%0], %1;" ::"r"(addr), "r"(a) : "memory"); }
__device__ __forceinline__ void sts64(uint32_t addr, uint32_t a, uint32_t b) { asm volatile("st.shared.v2.b32 [%0], {%1,%2};" ::"r"(addr), "r"(a), "r"(b) : "memory"); }
__device__ __forceinline__ uint32_t lds32(uint32_t addr) { uint32_t v; asm volatile("ld.shared.b32 %0, [%1];" : "=r"(v) : "r"(addr) : "memory"); return v; }
__device__ __forceinline__ uint2 lds64(uint32_t addr) { uint2 v; asm volatile("ld.shared.v2.b32 {%0,%1}, [%2];" : "=r"(v.x), "=r"(v.y) : "r"(addr) : "memory"); return v; }
__device__ __forceinline__ float2 lds64f(uint32_t addr) { float2 v; asm volatile("ld.shared.v2.f32 {%0,%1}, [%2];" : "=f"(v.x), "=f"(v.y) : "r"(addr) : "memory"); return v; }
__device__ __forceinline__ void ld_tag16(uint32_t* r, const uint4* p) {
  asm volatile("{\n.reg .b128 t;\nld.relaxed.gpu.global.b128 t, [%4];\nmov.b128 {%0,%1,%2,%3}, t;\n}" : "=r"(r[0]), "=r"(r[1]), "=r"(r[2]), "=r"(r[3]) : "l"(p) : "memory");
}
__device__ __forceinline__ uint2 ld_tag8(const uint2* p) {
  uint2 r;
  asm volatile("{\n.reg .b64 t;\nld.relaxed.gpu.global.b64 t, [%2];\nmov.b64 {%0,%1}, t;\n}" : "=r"(r.x), "=r"(r.y) : "l"(p) : "memory");
  return r;
}
__device__ __forceinline__ void st_tag16(uint4* p, const uint32_t* r) {
  asm volatile("{\n.reg .b128 t;\nmov.b128 t, {%1,%2,%3,%4};\nst.relaxed.gpu.global.b128 [%0], t;\n}" ::"l"(p), "r"(r[0]), "r"(r[1]), "r"(r[2]), "r"(r[3]) : "memory");
}
__device__ __forceinline__ void st_tag8(uint2* p, uint32_t a, uint32_t b) {
  asm volatile("{\n.reg .b64 t;\nmov.b64 t, {%1,%2};\nst.relaxed.gpu.global.b64 [%0], t;\n}" ::"l"(p), "r"(a), "r"(b) : "memory");
}
__device__ __forceinline__ uint32_t pack2(float lo, float hi) { uint32_t r; asm("cvt.rn.bf16x2.f32 %0, %1, %2;" : "=r"(r) : "f"(hi), "f"(lo)); return r; }
__device__ __forceinline__ float bf_lo(uint32_t v) { return __uint_as_float(v << 16); }
__device__ __forceinline__ float bf_hi(uint32_t v) { return __uint_as_float(v & 0xffff0000u); }
__device__ __forceinline__ float bf_round(float v) { return __bfloat162float(__float2bfloat16_rn(v)); }
__device__ __forceinline__ uint32_t hsub2(uint32_t a, uint32_t b) { uint32_t r; asm("sub.rn.bf16x2 %0, %1, %2;" : "=r"(r) : "r"(a), "r"(b)); return r; }
__device__ __forceinline__ uint32_t hmul2(uint32_t a, uint32_t b) { uint32_t r; asm("mul.rn.bf16x2 %0, %1, %2;" : "=r"(r) : "r"(a), "r"(b)); return r; }
__device__ __forceinline__ uint32_t hadd2(uint32_t a, uint32_t b) { uint32_t r; asm("add.rn.bf16x2 %0, %1, %2;" : "=r"(r) : "r"(a), "r"(b)); return r; }
__device__ __forceinline__ uint32_t hfma2(uint32_t a, uint32_t b, uint32_t c) { uint32_t r; asm("fma.rn.bf16x2 %0, %1, %2, %3;" : "=r"(r) : "r"(a), "r"(b), "r"(c)); return r; }
__device__ __forceinline__ float sqrt_hw(float x) { float r; asm("sqrt.approx.f32 %0, %1;" : "=f"(r) : "f"(x)); return r; }
__device__ __forceinline__ float tanh_hw(float x) { float r; asm("tanh.approx.f32 %0, %1;" : "=f"(r) : "f"(x)); return r; }
__device__ __forceinline__ uint32_t get_par() { mbar_wait(BAR_PAR, 0); return lds32(OFF_PAR); }

__device__ __forceinline__ uint64_t desc_k(uint32_t a16) { return 0x4000004000000000ull | ((a16 & 0x3fff) | (1u << 16)); }
__device__ __forceinline__ uint64_t desc_mn(uint32_t a16) { return 0x4000004000000000ull | ((a16 & 0x3fff) | ((8192u >> 4) << 16)); }
__host__ __device__ constexpr uint32_t pair_e(int pair) { return (sb + pair * 2 * UNIT) >> 4; }
__device__ __forceinline__ uint32_t bar_of(uint32_t e) { return (e >> 7) & 0x78; }
__device__ __forceinline__ uint32_t addr_of(uint32_t e) { return (e & 0x3fff) << 4; }

template <int TB> __device__ __forceinline__ void wgmma_rs_n128(float (&d)[64], const uint32_t* a, uint64_t db, int ob, int sd) {
  asm volatile("{\n.reg .pred p;\n.reg .b64 b;\nsetp.ne.b32 p, %70, 0;\nadd.u64 b, %68, %69;\n"
    "wgmma.mma_async.sync.aligned.m64n128k16.f32.bf16.bf16 {%0,%1,%2,%3,%4,%5,%6,%7,%8,%9,%10,%11,%12,%13,%14,%15,%16,%17,%18,%19,%20,%21,%22,%23,%24,%25,%26,%27,%28,%29,%30,%31,%32,%33,%34,%35,%36,%37,%38,%39,%40,%41,%42,%43,%44,%45,%46,%47,%48,%49,%50,%51,%52,%53,%54,%55,%56,%57,%58,%59,%60,%61,%62,%63}, "
    "{%64,%65,%66,%67}, b, p, 1, 1, %71;\n}"
    : "+f"(d[0]),"+f"(d[1]),"+f"(d[2]),"+f"(d[3]),"+f"(d[4]),"+f"(d[5]),"+f"(d[6]),"+f"(d[7]),"+f"(d[8]),"+f"(d[9]),"+f"(d[10]),"+f"(d[11]),"+f"(d[12]),"+f"(d[13]),"+f"(d[14]),"+f"(d[15]),"+f"(d[16]),"+f"(d[17]),"+f"(d[18]),"+f"(d[19]),"+f"(d[20]),"+f"(d[21]),"+f"(d[22]),"+f"(d[23]),"+f"(d[24]),"+f"(d[25]),"+f"(d[26]),"+f"(d[27]),"+f"(d[28]),"+f"(d[29]),"+f"(d[30]),"+f"(d[31]),"+f"(d[32]),"+f"(d[33]),"+f"(d[34]),"+f"(d[35]),"+f"(d[36]),"+f"(d[37]),"+f"(d[38]),"+f"(d[39]),"+f"(d[40]),"+f"(d[41]),"+f"(d[42]),"+f"(d[43]),"+f"(d[44]),"+f"(d[45]),"+f"(d[46]),"+f"(d[47]),"+f"(d[48]),"+f"(d[49]),"+f"(d[50]),"+f"(d[51]),"+f"(d[52]),"+f"(d[53]),"+f"(d[54]),"+f"(d[55]),"+f"(d[56]),"+f"(d[57]),"+f"(d[58]),"+f"(d[59]),"+f"(d[60]),"+f"(d[61]),"+f"(d[62]),"+f"(d[63])
    : "r"(a[0]), "r"(a[1]), "r"(a[2]), "r"(a[3]), "l"(db), "l"((uint64_t)ob), "r"(sd), "n"(TB));
}
template <int TB> __device__ __forceinline__ void wgmma_ss_n128(float (&d)[64], uint64_t da, int oa, uint64_t db, int ob, int sd) {
  asm volatile("{\n.reg .pred p;\n.reg .b64 a, b;\nsetp.ne.b32 p, %68, 0;\nadd.u64 a, %64, %65;\nadd.u64 b, %66, %67;\n"
    "wgmma.mma_async.sync.aligned.m64n128k16.f32.bf16.bf16 {%0,%1,%2,%3,%4,%5,%6,%7,%8,%9,%10,%11,%12,%13,%14,%15,%16,%17,%18,%19,%20,%21,%22,%23,%24,%25,%26,%27,%28,%29,%30,%31,%32,%33,%34,%35,%36,%37,%38,%39,%40,%41,%42,%43,%44,%45,%46,%47,%48,%49,%50,%51,%52,%53,%54,%55,%56,%57,%58,%59,%60,%61,%62,%63}, "
    "a, b, p, 1, 1, 0, %69;\n}"
    : "+f"(d[0]),"+f"(d[1]),"+f"(d[2]),"+f"(d[3]),"+f"(d[4]),"+f"(d[5]),"+f"(d[6]),"+f"(d[7]),"+f"(d[8]),"+f"(d[9]),"+f"(d[10]),"+f"(d[11]),"+f"(d[12]),"+f"(d[13]),"+f"(d[14]),"+f"(d[15]),"+f"(d[16]),"+f"(d[17]),"+f"(d[18]),"+f"(d[19]),"+f"(d[20]),"+f"(d[21]),"+f"(d[22]),"+f"(d[23]),"+f"(d[24]),"+f"(d[25]),"+f"(d[26]),"+f"(d[27]),"+f"(d[28]),"+f"(d[29]),"+f"(d[30]),"+f"(d[31]),"+f"(d[32]),"+f"(d[33]),"+f"(d[34]),"+f"(d[35]),"+f"(d[36]),"+f"(d[37]),"+f"(d[38]),"+f"(d[39]),"+f"(d[40]),"+f"(d[41]),"+f"(d[42]),"+f"(d[43]),"+f"(d[44]),"+f"(d[45]),"+f"(d[46]),"+f"(d[47]),"+f"(d[48]),"+f"(d[49]),"+f"(d[50]),"+f"(d[51]),"+f"(d[52]),"+f"(d[53]),"+f"(d[54]),"+f"(d[55]),"+f"(d[56]),"+f"(d[57]),"+f"(d[58]),"+f"(d[59]),"+f"(d[60]),"+f"(d[61]),"+f"(d[62]),"+f"(d[63])
    : "l"(da), "l"((uint64_t)oa), "l"(db), "l"((uint64_t)ob), "r"(sd), "n"(TB));
}
template <int TB> __device__ __forceinline__ void wgmma_rs_n64(float (&d)[32], const uint32_t* a, uint64_t db, int ob, int sd) {
  asm volatile("{\n.reg .pred p;\n.reg .b64 b;\nsetp.ne.b32 p, %38, 0;\nadd.u64 b, %36, %37;\n"
    "wgmma.mma_async.sync.aligned.m64n64k16.f32.bf16.bf16 {%0,%1,%2,%3,%4,%5,%6,%7,%8,%9,%10,%11,%12,%13,%14,%15,%16,%17,%18,%19,%20,%21,%22,%23,%24,%25,%26,%27,%28,%29,%30,%31}, "
    "{%32,%33,%34,%35}, b, p, 1, 1, %39;\n}"
    : "+f"(d[0]),"+f"(d[1]),"+f"(d[2]),"+f"(d[3]),"+f"(d[4]),"+f"(d[5]),"+f"(d[6]),"+f"(d[7]),"+f"(d[8]),"+f"(d[9]),"+f"(d[10]),"+f"(d[11]),"+f"(d[12]),"+f"(d[13]),"+f"(d[14]),"+f"(d[15]),"+f"(d[16]),"+f"(d[17]),"+f"(d[18]),"+f"(d[19]),"+f"(d[20]),"+f"(d[21]),"+f"(d[22]),"+f"(d[23]),"+f"(d[24]),"+f"(d[25]),"+f"(d[26]),"+f"(d[27]),"+f"(d[28]),"+f"(d[29]),"+f"(d[30]),"+f"(d[31])
    : "r"(a[0]), "r"(a[1]), "r"(a[2]), "r"(a[3]), "l"(db), "l"((uint64_t)ob), "r"(sd), "n"(TB));
}
template <int TB> __device__ __forceinline__ void wgmma_ss_n64(float (&d)[32], uint64_t da, int oa, uint64_t db, int ob, int sd) {
  asm volatile("{\n.reg .pred p;\n.reg .b64 a, b;\nsetp.ne.b32 p, %36, 0;\nadd.u64 a, %32, %33;\nadd.u64 b, %34, %35;\n"
    "wgmma.mma_async.sync.aligned.m64n64k16.f32.bf16.bf16 {%0,%1,%2,%3,%4,%5,%6,%7,%8,%9,%10,%11,%12,%13,%14,%15,%16,%17,%18,%19,%20,%21,%22,%23,%24,%25,%26,%27,%28,%29,%30,%31}, "
    "a, b, p, 1, 1, 0, %37;\n}"
    : "+f"(d[0]),"+f"(d[1]),"+f"(d[2]),"+f"(d[3]),"+f"(d[4]),"+f"(d[5]),"+f"(d[6]),"+f"(d[7]),"+f"(d[8]),"+f"(d[9]),"+f"(d[10]),"+f"(d[11]),"+f"(d[12]),"+f"(d[13]),"+f"(d[14]),"+f"(d[15]),"+f"(d[16]),"+f"(d[17]),"+f"(d[18]),"+f"(d[19]),"+f"(d[20]),"+f"(d[21]),"+f"(d[22]),"+f"(d[23]),"+f"(d[24]),"+f"(d[25]),"+f"(d[26]),"+f"(d[27]),"+f"(d[28]),"+f"(d[29]),"+f"(d[30]),"+f"(d[31])
    : "l"(da), "l"((uint64_t)oa), "l"(db), "l"((uint64_t)ob), "r"(sd), "n"(TB));
}

struct RowStat {
  uint32_t m2, rh, rl;
  __device__ __forceinline__ uint32_t norm_half(uint32_t x) const { uint32_t d = hsub2(x, m2); return hfma2(d, rh, hmul2(d, rl)); }
  __device__ __forceinline__ void resid(float& a, float& b, uint32_t x, uint32_t d2) const {
    uint32_t t = hmul2(norm_half(x), d2);
    a = bf_lo(x) + bf_lo(t); b = bf_hi(x) + bf_hi(t);
  }
};
__device__ __forceinline__ RowStat row_stat(uint2 s) { return RowStat{__byte_perm(s.x, 0, 0x1010), __byte_perm(s.x, 0, 0x3232), __byte_perm(s.y, 0, 0x1010)}; }
__device__ __forceinline__ uint2 encode_stat(float sum, float sumsq) {
  const float mean = sum * (1.f / DM), var = fmaxf(fmaf(-mean, mean, sumsq * (1.f / DM)), 0.f);
  const float r = __fdividef(0.5f, bf_round(sqrt_hw(bf_round(bf_round(var) + 1e-5f)))), rhi = bf_round(r);
  return make_uint2(pack2(mean, rhi), pack2(r - rhi, 0.f));
}
__device__ __forceinline__ void publish_stats(const __nv_bfloat16* x, int row, int lane) {
  const uint2* xp = reinterpret_cast<const uint2*>(x + (size_t)row * DM) + (lane & 15);
  const uint32_t par = (g_epoch[blockIdx.x] + 1) & 1;
  uint2 v[9];
#pragma unroll
  for (int i = 0; i < 9; i++) v[i] = __ldg(xp + 16 * i);
  float s = 0.f, q = 0.f;
#pragma unroll
  for (int i = 0; i < 9; i++) {
    const float a = bf_lo(v[i].x), b = bf_hi(v[i].x), c = bf_lo(v[i].y), d = bf_hi(v[i].y);
    s += (a + b) + (c + d);
    q += fmaf(a, a, b * b) + fmaf(c, c, d * d);
  }
#pragma unroll
  for (int o = 1; o < 16; o <<= 1) { s += __shfl_xor_sync(~0u, s, o); q += __shfl_xor_sync(~0u, q, o); }
  const uint2 st = encode_stat(s, q);
  if ((lane & 15) == 0) st_tag8(g_stats + row, st.x, st.y | (par << 16));
}
__device__ __forceinline__ uint32_t load_x_frags(uint32_t (&xa)[144], uint32_t (&n)[4], uint32_t fa, uint32_t bar, uint32_t xpar, uint32_t zero, const uint2* sp, int row, int lane) {
  uint32_t dep = 0;
  uint2 s0, s1;
#pragma unroll
  for (int g = 0; g < 3; g++) {
    mbar_wait(bar + g * 8, xpar);
    if (g == 2) { s0 = ld_tag8(sp); s1 = ld_tag8(sp + 8); }
#pragma unroll
    for (int i = 12 * g; i < 12 * g + 12; i++) ldsm4(&xa[4 * i], (fa ^ ((i & 3) << 5)) + (i >> 2) * UNIT);
#pragma unroll
    for (int i = 12 * g; i < 12 * g + 12; i++) dep |= xa[4 * i];
  }
  const uint32_t par = get_par();
  while (__any_sync(~0u, ((s0.y >> 16) != par) | ((s1.y >> 16) != par))) { s0 = ld_tag8(sp); s1 = ld_tag8(sp + 8); }
  if ((lane & 3) == 0) { sts64(OFF_STATS + row * 8, s0.x, s0.y); sts64(OFF_STATS + row * 8 + 64, s1.x, s1.y); }
  const float c0 = -bf_lo(s0.x) * bf_hi(s0.x), c1 = -bf_lo(s1.x) * bf_hi(s1.x);
  n[0] = __byte_perm(s0.x, 0, 0x3232); n[1] = pack2(c0, c0); n[2] = __byte_perm(s1.x, 0, 0x3232); n[3] = pack2(c1, c1);
  return dep & zero;
}
__device__ __forceinline__ void norm_blocks(uint32_t (&xa)[144], int b0, int b1, const uint32_t (&n)[4], uint32_t z) {
  const uint32_t c0 = n[1] ^ z, c1 = n[3] ^ z;
#pragma unroll
  for (int i = 16 * b0; i < 16 * b1; i += 2) { xa[i] = hfma2(xa[i], n[0], c0); xa[i + 1] = hfma2(xa[i + 1], n[2], c1); }
}

__device__ __forceinline__ uint32_t ring_get(uint32_t e) {
  mbar_wait(BAR_FULL + bar_of(e), e >> 31);
  return e;
}
__device__ __forceinline__ void ring_put(uint32_t e, uint32_t dep = 0) { mbar_arrive_w(BAR_EMPTY + bar_of(e) + dep); }
__device__ __forceinline__ void hand_over(int pair, uint32_t dep = 0) { mbar_arrive_w(BAR_EMPTY + pair * 8 + dep); }

template <int TB, class F>
__device__ __forceinline__ void tile_rs(float (&acc)[64], uint32_t (&xa)[144], const uint32_t* tab, int wg, int skew_bar, F shadow) {
  uint32_t prev = 0;
  if (wg == 1) bar_sync(skew_bar, 256);
#pragma unroll
  for (int kb = 0; kb < 9; kb++) {
    const uint32_t e = tab[kb], ba = ring_get(e);
    const uint64_t db = TB ? desc_mn(ba) : desc_k(ba);
    wg_fence();
#pragma unroll
    for (int ks = 0; ks < 4; ks++) wgmma_rs_n128<TB>(acc, &xa[kb * 16 + ks * 4], db, TB ? ks * 128 : ks * 2, (kb | ks) != 0);
    wg_commit();
    if (kb == SKEW - 1 && wg == 0) bar_arrive(skew_bar, 256);
    shadow(kb);
    if (kb > 0) { wg_wait<1>(); ring_put(prev); }
    prev = e;
  }
  wg_wait<0>();
  ring_put(prev);
  fence_regs(acc);
}
__device__ __forceinline__ uint32_t glu2(const float (&acc)[64], int i) {
  const float u0 = acc[32 + 2 * i], u1 = acc[33 + 2 * i];
  return pack2(fmaf(u0, tanh_hw(acc[2 * i]), u0), fmaf(u1, tanh_hw(acc[2 * i + 1]), u1));
}
__device__ __forceinline__ void stash_v(const float (&acc)[64], uint32_t wb, int row, int lane) {
  const uint32_t b = wb + (row & 63) * 256 + (lane & 3) * 8 + (lane & 12) * 8;
#pragma unroll
  for (int G = 0; G < 8; G++) {
    const uint32_t a = (b ^ ((G & 3) << 5)) + ((G & 4) << 5);
    sts64(a, pack2(acc[4 * G], acc[32 + 4 * G]), pack2(acc[4 * G + 1], acc[33 + 4 * G]));
    sts64(a + 8 * 256, pack2(acc[4 * G + 2], acc[34 + 4 * G]), pack2(acc[4 * G + 3], acc[35 + 4 * G]));
  }
}

__device__ __forceinline__ uint4* part_ptr(int m, int owner, int sender) { return g_part + (size_t)((m * 9 + owner) * 9 + sender) * 1024; }
template <int N>
__device__ __forceinline__ void pack_part(uint32_t* pk, const float (&a)[N], uint32_t par) {
#pragma unroll
  for (int i = 0; i < N / 2; i++) { pk[i] = pack2(a[2 * i], a[2 * i + 1]); if (!(i & 1)) pk[i] = (pk[i] & ~1u) | par; }
}
__device__ __forceinline__ void recv_issue(uint32_t* t, const uint4* src) {
#pragma unroll
  for (int i = 0; i < 4; i++) ld_tag16(&t[4 * i], src + i * 32);
}
__device__ __forceinline__ void recv_check(uint32_t* t, const uint4* src, uint32_t par) {
  while (__any_sync(~0u, ((t[0] ^ par) | (t[4] ^ par) | (t[8] ^ par) | (t[12] ^ par)) & 1)) recv_issue(t, src);
}
__device__ __forceinline__ void recv_add(float (&R)[32], const uint32_t* t, int i0, int i1) {
#pragma unroll
  for (int i = i0; i < i1; i++) { R[2 * i] += bf_lo(t[i]); R[2 * i + 1] += bf_hi(t[i]); }
}
__device__ __forceinline__ void store_out(const float (&R)[32], float* o, int lane) {
  o += (lane & 1) * 8 + (lane & 2) * 2;
  const bool odd = lane & 1;
#pragma unroll
  for (int i = 0; i < 8; i++) {
    const int k = (i >> 1) * 8 + (i & 1) * 2;
    const float r0 = __shfl_xor_sync(~0u, odd ? R[k] : R[k + 4], 1), r1 = __shfl_xor_sync(~0u, odd ? R[k + 1] : R[k + 5], 1);
    __stcs(reinterpret_cast<float4*>(o + (i >> 1) * 16 + (i & 1) * 8 * DM), odd ? make_float4(r0, r1, R[k + 4], R[k + 5]) : make_float4(R[k], R[k + 1], r0, r1));
  }
}
__device__ __forceinline__ void mma_g8(float (&acc)[32], uint32_t are, uint32_t aim, uint32_t cb) {
  wg_fence();
#pragma unroll
  for (int ks = 0; ks < 4; ks++) wgmma_ss_n64<0>(acc, desc_k(are), ks * 2, desc_k(cb), ks * 2, ks != 0);
#pragma unroll
  for (int ks = 0; ks < 4; ks++) wgmma_ss_n64<0>(acc, desc_k(aim), ks * 2, desc_k(cb), 512 + ks * 2, 1);
  wg_commit();
}

__device__ __forceinline__ float2 cmad(float2 a, float2 b, float2 c) {
  return make_float2(fmaf(a.x, b.x, fmaf(-a.y, b.y, c.x)), fmaf(a.x, b.y, fmaf(a.y, b.x, c.y)));
}
__device__ __forceinline__ float2 csq(float2 a) { return make_float2(fmaf(a.x, a.x, -a.y * a.y), 2.f * a.x * a.y); }
__device__ __forceinline__ void ssm_coef(const Params& p, int ch, float2& lam, float2& coef) {
  float a = __bfloat162float(p.lam_re[ch]), b = __bfloat162float(p.lam_im[ch]);
  float dt = bf_round(expf(__bfloat162float(p.log_dt[ch])));
  float e = expf(dt * a), sn, cs;
  sincospif(dt * b * 0.318309886183790672f, &sn, &cs);
  lam.x = e * cs; lam.y = e * sn;
  float nr = lam.x - 1.f, inv = __fdividef(4.f, a * a + b * b);
  coef.x = (nr * a + lam.y * b) * inv; coef.y = (lam.y * a - nr * b) * inv;
}
template <int NSEG>
__device__ __forceinline__ void ssm_scan(float2 lam, float2 coef, int c, int seg, int grp, int m, uint32_t par, uint32_t zero) {
  constexpr int TPW = 128 / NSEG, LB = NSEG > 1 ? 8 : 4;
  const int tb = seg * TPW;
  float2 s = {0.f, 0.f};
  uint32_t v[8], sa0 = sb + (tb >> 6) * WREG + (tb & 63) * 256 + c * 4;
  asm volatile("" : "+r"(sa0));
  uint32_t sa = sa0;
#pragma unroll
  for (int u = 0; u < 8; u++) v[u] = lds32((sa ^ ((u & 3) << 5)) + u * 256);
#pragma unroll 1
  for (int i = 0; i < TPW / 8; i++) {
    sa += (NSEG == 1 && i == 7) ? WREG - 7 * 2048 : 2048;
#pragma unroll
    for (int u = 0; u < 8; u++) {
      s = cmad(lam, s, make_float2(bf_lo(v[u]), bf_hi(v[u])));
      v[u] = lds32((sa ^ ((u & 3) << 5)) + u * 256);
    }
  }
  float2 pw = lam;
#pragma unroll 1
  for (int k = 1; k < TPW; k <<= 1) pw = csq(pw);
  const uint32_t xch = sb + 9 * UNIT + c * 8;
  if (NSEG > 1) {
    sts64(xch + seg * 512, __float_as_uint(s.x), __float_as_uint(s.y));
    bar_sync(5, 256);
    if (seg == NSEG - 1) {
      s = make_float2(0.f, 0.f);
#pragma unroll 1
      for (int w = 0; w < NSEG; w++) s = cmad(pw, s, lds64f(xch + w * 512));
    }
  }
  uint2* st = g_state + grp * 16 * 64 + c;
  if (seg == NSEG - 1) st_tag8(st + m * 64, (__float_as_uint(s.x) & ~1u) | par, __float_as_uint(s.y));
  float2 pl = pw;
#pragma unroll 1
  for (int k = TPW; k < 128; k <<= 1) pl = csq(pl);
  s = make_float2(0.f, 0.f);
#pragma unroll 1
  for (int k = m; k > 0; k -= LB, st += LB * 64) {
    uint2 a[LB];
    uint32_t it = 0, bad;
    do {
      if (++it > (1u << 21)) __trap();
      bad = 0;
#pragma unroll
      for (int i = 0; i < LB; i++) { a[i].x = par; if (i < k) a[i] = ld_tag8(st + i * 64); }
#pragma unroll
      for (int i = 0; i < LB; i++) bad |= a[i].x ^ par;
    } while (__any_sync(~0u, bad & 1));
#pragma unroll
    for (int i = 0; i < LB; i++)
      if (i < k) s = cmad(pl, s, make_float2(__uint_as_float(a[i].x), __uint_as_float(a[i].y)));
  }
  if (NSEG > 1) {
#pragma unroll 1
    for (int w = 0; w < seg; w++) s = cmad(pw, s, lds64f(xch + w * 512));
  }
  sa = sa0;
  uint32_t* hg = reinterpret_cast<uint32_t*>(g_hs + (size_t)(m * 128 + tb) * 1152 + grp * 128) + ((sa0 & 255) >> 3) + (sa0 & 4) * 8;
  const uint32_t sel = (sa0 & 4) ? 0x3276 : 0x5410;
#pragma unroll
  for (int u = 0; u < 4; u++) v[u] = lds32((sa ^ (u << 5)) + u * 256);
#pragma unroll 1
  for (int i = 0; i < TPW / 4; i++) {
    sa += (NSEG == 1 && i == 15) ? WREG - 15 * 1024 : 1024;
    uint32_t y[4];
#pragma unroll
    for (int u = 0; u < 4; u++) {
      s = cmad(lam, s, make_float2(bf_lo(v[u]), bf_hi(v[u])));
      y[u] = pack2(fmaf(coef.x, s.x, -coef.y * s.y), fmaf(-coef.x, s.y, -coef.y * s.x));
      v[u] = __shfl_xor_sync(~0u, y[u], 1);
    }
#pragma unroll
    for (int u = 0; u < 4; u++) {
      hg[u * 576] = __byte_perm(y[u], v[u], sel);
      v[u] = lds32((sa ^ (u << 5)) + u * 256);
    }
    hg += 4 * 576;
  }
  if (NSEG > 1) mbar_arrive_w(BAR_P1 + (v[0] & v[1] & v[2] & v[3] & zero));
  fence_async_all();
  __syncwarp();
}

__host__ __device__ constexpr int kb_tile(int kk) { return kk < 4 ? kk : kk == 4 ? 8 : kk - 1; }
template <int N>
__device__ __forceinline__ void mma_block(float (&acc)[N / 2], const uint32_t (&hr)[80], int kk, uint64_t da, uint32_t ba, bool first) {
  const uint64_t db = kk >= 9 ? desc_k(ba) : desc_mn(ba);
  const int oa = (kk < 4 ? 7 - kk : kk - 9) * (UNIT >> 4);
#pragma unroll
  for (int ks = 0; ks < 4; ks++) {
    const int sd = !(first && ks == 0);
    if (kk >= 9) {
      if constexpr (N == 128) wgmma_ss_n128<0>(acc, da, oa + ks * 2, db, ks * 2, sd); else wgmma_ss_n64<0>(acc, da, oa + ks * 2, db, ks * 2, sd);
    } else if (kk < 4) {
      if constexpr (N == 128) wgmma_ss_n128<1>(acc, da, oa + ks * 2, db, ks * 128, sd); else wgmma_ss_n64<1>(acc, da, oa + ks * 2, db, ks * 128, sd);
    } else {
      if constexpr (N == 128) wgmma_rs_n128<1>(acc, &hr[(kk - 4) * 16 + ks * 4], db, ks * 128, sd);
      else wgmma_rs_n64<1>(acc, &hr[(kk - 4) * 16 + ks * 4], db, ks * 128, sd);
    }
  }
}

__device__ __forceinline__ void spare_scan(const Params& p, int m, int r, int w8, int lane) {
  const uint32_t par = get_par();
  float2 lam, coef;
  ssm_coef(p, 512 + (w8 & 1) * 32 + lane, lam, coef);
  bar_sync(5, 256);
  mbar_arrive_w(BAR_STASH);
  ssm_scan<4>(lam, coef, (w8 & 1) * 32 + lane, w8 >> 1, 8, m, par, p.zero);
  mbar_arrive_w(BAR_SCAN);
}
__device__ __forceinline__ void spare_atom8(const Params& p, const uint32_t* tab, int m, int wg, int w8, int lane) {
  float acc[32];
  const uint32_t are = ring_get(tab[0]), aim = ring_get(tab[1]), cb = ring_get(tab[2]);
  mma_g8(acc, are + wg * 512, aim + wg * 512, cb);
  wg_wait<0>();
  ring_put(tab[0]); ring_put(tab[1]); ring_put(tab[2]);
  fence_regs(acc);
  uint32_t pk[16];
  pack_part(pk, acc, get_par());
#pragma unroll
  for (int i = 0; i < 4; i++) st_tag16(part_ptr(m, 8, 8) + w8 * 128 + lane + i * 32, &pk[4 * i]);
}

struct Who {
  int tid;
  __device__ __forceinline__ int wg() const { return tid >> 7; }
  __device__ __forceinline__ int w8() const { return tid >> 5; }
  __device__ __forceinline__ int lane() const { return tid & 31; }
  __device__ __forceinline__ int row() const { return (tid >> 5) * 16 + ((tid & 31) >> 2); }
  __device__ __forceinline__ uint32_t wb() const { return sb + (tid >> 7) * WREG; }
  __device__ __forceinline__ uint32_t frag() const { return (((tid >> 5) & 3) * 16 + (tid & 15)) * 128 + ((((tid >> 4) & 1) ^ (tid & 7)) << 4); }
};
__device__ __forceinline__ Who who() { Who w; asm volatile("mov.u32 %0, %%tid.x;" : "=r"(w.tid)); return w; }

__device__ __forceinline__ void consumer(const Params& p, bool spare, int m, int j) {
  const int wg = threadIdx.x >> 7;
  if (!spare) publish_stats(p.xg, m * 128 + j * 16 + (threadIdx.x >> 4), threadIdx.x & 31);
  bar_sync(6, 288);
  uint32_t hr[80];
  {
    uint32_t xa[144];
    float acc[64];
#pragma unroll 1
    for (int r = 0;; r++) {
      hand_over(6 - 5 * wg); hand_over(7 - 5 * wg); hand_over(9 - 5 * wg);
      uint32_t n[4];
      {
        const Who w = who();
        const uint32_t dep = load_x_frags(xa, n, w.wb() + w.frag(), BAR_X + wg * 24, r & 1, p.zero, g_stats + (m + 4 * r) * 128 + w.row(), w.row(), w.lane());
        hand_over(1 + 5 * wg, dep); hand_over(2 + 5 * wg, dep); hand_over(4 + 5 * wg, dep);
      }
      norm_blocks(xa, 0, AHEAD, n, 0);
      tile_rs<0>(acc, xa, spare ? p.sched_sp + (r ? 12 * r - 3 : 0) : p.sched, wg, 2, [&](int kb) {
        if (kb + AHEAD < 9) norm_blocks(xa, kb + AHEAD, kb + AHEAD + 1, n, who().tid & p.zero);
      });
      const Who w = who();
      stash_v(acc, w.wb(), w.row(), w.lane());
      if (!spare) break;
      spare_scan(p, m + 4 * r, r, w.w8(), w.lane());
#pragma unroll 1
      for (int q = r > 0 ? r - 1 : 1; q <= (r == 3 ? 3 : r - 1); q++) spare_atom8(p, p.sched_sp + 12 * q + (q < 3 ? 18 : 9), m + 4 * q, wg, w.w8(), w.lane());
      if (r == 3) { mbar_arrive_w(BAR_DONE); return; }
    }
    __syncwarp();
    mbar_arrive_w(BAR_STASH);
#pragma unroll 1
    for (int t = 0;; t++) {
      uint32_t ha;
      tile_rs<1>(acc, xa, p.sched + 9 + 9 * t, wg, 1 + (t & 1), [&](int kb) {
        if (kb < 8) return;
        const Who w = who();
        ha = w.wb() + w.frag();
        const uint32_t rc = p.reclaim[wg][t & 7];
        if (rc) mbar_wait(BAR_EMPTY + bar_of(rc), rc >> 31);
        if (t == 6) {
          mbar_wait(BAR_SCAN, 0);
          fence_async();
          bar_sync(3 + wg, 128);
        }
      });
      if (t == 8) {
        __syncwarp();
#pragma unroll
        for (int b = 0; b < 4; b++)
#pragma unroll
          for (int ks = 0; ks < 4; ks++) ldsm4(&hr[16 + b * 16 + ks * 4], (ha ^ (ks << 5)) + (3 - b) * UNIT);
        break;
      }
      ha += (7 - t) * UNIT;
#pragma unroll
      for (int ks = 0; ks < 4; ks++) {
        uint32_t h[4];
#pragma unroll
        for (int i = 0; i < 4; i++) h[i] = glu2(acc, ks * 4 + i);
        stsm4(ha ^ (ks << 5), h);
      }
    }
#pragma unroll
    for (int i = 0; i < 16; i++) hr[i] = glu2(acc, i);
  }
  {
    uint32_t dep = 0;
#pragma unroll
    for (int i = 16; i < 80; i += 4) dep |= hr[i];
    dep &= p.zero;
    hand_over(0, dep); hand_over(5, dep); hand_over(1, dep); hand_over(6, dep);
  }
  const uint32_t par = get_par();
  uint4* const pb = part_ptr(m, 0, 0) + who().w8() * 128 + who().lane();
  auto src = [&](int d) { return pb + (j * 9 + ((j - d) & 7)) * 1024; };
  auto dst = [&](int d) { return pb + ((d ? (j + d) & 7 : 8) * 9 + j) * 1024; };
  const uint32_t* tab = p.sched + 90;
  const uint64_t da = desc_k(__shfl_sync(~0u, who().wb() >> 4, 0));
  float R[32];
  uint32_t pk[32];
#pragma unroll 1
  for (int ps = 0; ps < 4; ps++) {
    float acc[64];
    uint32_t prev = 0, prev2 = 0, ex = 0;
    if (wg == 1) bar_sync(2 - (ps & 1), 256);
#pragma unroll
    for (int kk = 0; kk < 11; kk++) {
      const uint32_t e = tab[kk], ba = ring_get(e);
      if (kk == 9 && ps == 0) mbar_wait(BAR_FULL + wg * 5 * 8, p.sched[NSLOT + wg] >> 31);
      wg_fence();
      mma_block<128>(acc, hr, kk, da, ba, kk == 0);
      wg_commit();
      if (kk == SKEW2 - 1 && wg == 0) bar_arrive(2 - (ps & 1), 256);
      uint32_t dep = 0;
      if (kk >= 6 && ps == 0) {
        if (kk == 6) {
          ex = ring_get(tab[7]);
          tab++;
          const Who w = who();
          const uint32_t xb = addr_of(ex) + wg * UNIT + w.frag();
#pragma unroll
          for (int ks = 0; ks < 4; ks++) {
            ldsm4(&pk[4 * ks], xb ^ (ks << 5));
            const uint2 d = lds64(OFF_DSK + ks * 32 + (w.lane() & 3) * 8);
            pk[16 + 2 * ks] = d.x; pk[17 + 2 * ks] = d.y;
          }
          const uint2 s0 = lds64(OFF_STATS + w.row() * 8), s1 = lds64(OFF_STATS + w.row() * 8 + 64);
          pk[24] = s0.x; pk[25] = s0.y; pk[26] = s1.x; pk[27] = s1.y;
        } else {
          const RowStat a = row_stat(make_uint2(pk[24], pk[25])), b = row_stat(make_uint2(pk[26], pk[27]));
          if (kk == 7) ring_put(ex, (pk[0] | pk[4] | pk[8] | pk[12]) & p.zero);
#pragma unroll
          for (int i = 4 * kk - 28; i < 4 * kk - 24; i++) {
            ((i & 1) ? b : a).resid(R[2 * i], R[2 * i + 1], pk[i], pk[16 + (i >> 1)]);
            dep |= __float_as_uint(R[2 * i]) | __float_as_uint(R[2 * i + 1]);
          }
          dep &= p.zero;
        }
      }
      if (kk < 8 && ps > 0) st_tag16(dst(2 * ps - 2 + (kk >> 2)) + (kk & 3) * 32, &pk[kk * 4]);
      if (kk == 6 && ps == 1) mbar_arrive_w(BAR_P1);
      if (ps > 1) {
        if (kk == 5) recv_issue(pk, src(2 * ps - 3));
        if (kk == 7) { recv_check(pk, src(2 * ps - 3), par); recv_add(R, pk, 0, 8); }
        if (kk == 8) { if (ps == 3) recv_issue(pk + 16, src(2)); recv_add(R, pk, 8, 16); }
        if (kk == 10 && ps == 3) { recv_check(pk + 16, src(2), par); recv_add(R, pk + 16, 0, 16); }
      }
      if (kk >= 2) { wg_wait<2>(); ring_put(prev2, dep); }
      prev2 = prev; prev = e;
    }
    tab += 11;
    wg_wait<1>();
    ring_put(prev2);
    wg_wait<0>();
    ring_put(prev);
    fence_regs(acc);
    pack_part(pk, acc, par);
  }
  {
    float acc[32];
    uint32_t t[16];
    recv_issue(t, src(4));
#pragma unroll
    for (int i = 0; i < 8; i++) st_tag16(dst(6 + (i >> 2)) + (i & 3) * 32, &pk[i * 4]);
    if (wg == 1) bar_sync(2, 256);
    {
      const uint32_t are = ring_get(tab[0]), aim = ring_get(tab[1]), cb = ring_get(tab[2]);
      mma_g8(acc, are + wg * 512, aim + wg * 512, cb);
    }
#pragma unroll
    for (int s = 0; s < 6; s++) {
      const uint32_t ba = ring_get(tab[3 + s]);
      wg_fence();
      mma_block<64>(acc, hr, 2 * s, da, ba, false);
      if (s < 5) mma_block<64>(acc, hr, 2 * s + 1, da, ba + 512, false);
      wg_commit();
      if (s == 0) {
        if (wg == 0) bar_arrive(2, 256);
        wg_wait<1>();
        ring_put(tab[0]);
      }
      if (s == 1) { recv_check(t, src(4), par); recv_add(R, t, 0, 16); recv_issue(t, src(5)); }
      if (s == 3) { recv_check(t, src(5), par); recv_add(R, t, 0, 16); }
      if (s == 5) { recv_issue(pk + 16, src(6)); recv_issue(pk, src(7)); }
    }
    wg_wait<0>();
    fence_regs(acc);
#pragma unroll
    for (int i = 0; i < 32; i++) R[i] += acc[i];
    recv_check(pk + 16, src(6), par);
    recv_check(pk, src(7), par);
#pragma unroll
    for (int i = 0; i < 16; i++) t[i] = hadd2(pk[16 + i], pk[i]);
    recv_add(R, t, 0, 16);
    const Who w = who();
    store_out(R, p.out + (size_t)(m * 128 + w.row()) * DM + j * 64, w.lane());
    mbar_arrive_w(BAR_DONE);
  }
}

__device__ __forceinline__ void load_x(const Params& p, int m, int wg, int g0, int g1) {
#pragma unroll 1
  for (int g = g0; g < g1; g++) {
    mbar_expect_tx(BAR_X + (wg * 3 + g) * 8, 3 * UNIT);
    tma_load3(sb + wg * WREG + g * 3 * UNIT, &p.x, 0, m * 128 + wg * 64, g * 3, BAR_X + (wg * 3 + g) * 8);
  }
}
__device__ __forceinline__ uint32_t slot_acquire(uint32_t e, uint32_t bytes) {
  const uint32_t bar = BAR_FULL + bar_of(e);
  if (!(e & 0x8000)) mbar_wait_b(bar + (BAR_EMPTY - BAR_FULL), (e >> 30) & 1);
  mbar_expect_tx(bar, bytes);
  return bar;
}
__device__ __forceinline__ void load_slot(uint32_t e, const CUtensorMap* m0, int a0, int b0, const CUtensorMap* m1, int a1, int b1) {
  const uint32_t dst = addr_of(e), bar = slot_acquire(e, m1 ? 2 * UNIT : UNIT);
  tma_load(dst, m0, a0, b0, bar);
  if (m1) tma_load(dst + UNIT, m1, a1, b1, bar);
}
__device__ __forceinline__ const CUtensorMap* p2_box(const Params& p, int j, int kk, int a, int& c0, int& c1) {
  if (kk >= 9) { c0 = 64 * j; c1 = 64 * a; return kk == 9 ? &p.cre : &p.cim; }
  c0 = 64 * a; c1 = DM * j + 64 * kb_tile(kk);
  return &p.wd;
}
__device__ __forceinline__ void load_g8(const Params& p, const uint32_t* tab, int m, int a) {
#pragma unroll 1
  for (int k = 0; k < 2; k++) load_slot(tab[k], &p.hs, 1024 + 64 * k, m * 128, &p.hs, 1024 + 64 * k, m * 128 + 64);
  load_slot(tab[2], &p.cre, 512, 64 * a, &p.cim, 512, 64 * a);
}
__device__ __forceinline__ void producer_main(const Params& p, int m, int j) {
  const uint32_t* tab = p.sched;
#pragma unroll 1
  for (int kb = 0; kb < 9; kb++) {
    load_slot(*tab++, &p.bre, 64 * kb, 64 * j, &p.bim, 64 * kb, 64 * j);
    if (kb == 0) mbar_wait_b(BAR_X, 0);
    if (kb >= 1 && kb < 4) load_x(p, m, 1, kb - 1, kb);
  }
#pragma unroll 1
  for (int c = DM * j; c < DM * j + DM; c += 64)
#pragma unroll 1
    for (int k = 0; k < DM; k += 64) load_slot(*tab++, &p.wg, c, k, &p.wu, c, k);
  mbar_wait_b(BAR_SCAN, 0);
  tma_prefetch(&p.x2, 64 * j, m * 128);
#pragma unroll 1
  for (int k = 0; k < 4; k++) tma_prefetch(&p.hs, 128 * j + 64 * (k & 1), m * 128 + 32 * (k & 2));
#pragma unroll 1
  for (int ps = 0; ps < 4; ps++)
#pragma unroll 1
    for (int kk = 0; kk < 11; kk++) {
      int a0, b0, a1, b1;
      const CUtensorMap* mp = p2_box(p, j, kk, ps == 0 ? 8 : (j + 2 * ps) & 7, a0, b0);
      p2_box(p, j, kk, (j + 2 * ps + 1) & 7, a1, b1);
      load_slot(*tab++, mp, a0, b0, mp, a1, b1);
      if (kk == 6 && ps == 0) {
        const uint32_t e = *tab++, bar = slot_acquire(e, 2 * UNIT);
        tma_load(addr_of(e), &p.x2, 64 * j, m * 128, bar);
#pragma unroll 1
        for (int w = 0; w < 2; w++) load_slot(p.sched[NSLOT + w], &p.hs, 128 * j, m * 128 + w * 64, &p.hs, 128 * j + 64, m * 128 + w * 64);
      }
    }
  mbar_wait_b(BAR_G8, 0);
  load_g8(p, tab, m, j);
  tab += 3;
#pragma unroll 1
  for (int s = 0; s < 6; s++) {
    int a0, b0, a1 = 0, b1 = 0;
    const CUtensorMap* m0 = p2_box(p, j, 2 * s, j, a0, b0);
    const CUtensorMap* m1 = s < 5 ? p2_box(p, j, 2 * s + 1, j, a1, b1) : nullptr;
    load_slot(*tab++, m0, a0, b0, m1, a1, b1);
  }
}
__device__ __forceinline__ void producer_spare(const Params& p, int s) {
  const uint32_t* tab = p.sched_sp;
  load_x(p, s, 1, 0, 3);
#pragma unroll 1
  for (int m = s; m < 16; m += 4) {
#pragma unroll 1
    for (int kb = 0; kb < 9; kb++) load_slot(*tab++, &p.bre, 64 * kb, 512, &p.bim, 64 * kb, 512);
    mbar_wait_b(BAR_STASH, (m >> 2) & 1);
    if (m < 12) { load_x(p, m + 4, 0, 1, 3); load_x(p, m + 4, 1, 1, 3); }
    if (m >= 4) { load_g8(p, tab, m - 4, 8); tab += 3; }
    mbar_wait_b(BAR_P1, (m >> 2) & 1);
    if (m < 12) { load_x(p, m + 4, 0, 0, 1); load_x(p, m + 4, 1, 0, 1); }
    mbar_wait_b(BAR_SCAN, (m >> 2) & 1);
  }
  load_g8(p, tab, s + 12, 8);
}

__device__ __forceinline__ void scan_worker(const Params& p, int m, int j, int c) {
  float2 lam, coef;
  ssm_coef(p, 64 * j + c, lam, coef);
  mbar_wait_b(BAR_STASH, 0);
  ssm_scan<1>(lam, coef, c, 0, j, m, get_par(), 0);
  mbar_arrive_w(BAR_SCAN);
}
template <int N>
__device__ __forceinline__ void sum_pieces(float (&v)[4], const uint2* src, uint32_t par) {
  uint2 a[N];
  uint32_t it = 0, bad;
  src += who().lane() * 2;
  while (true) {
    bad = 0;
#pragma unroll
    for (int i = 0; i < N; i++) a[i] = ld_tag8(src + i * 2048);
#pragma unroll
    for (int i = 0; i < N; i++) bad |= a[i].x ^ par;
    if (!__any_sync(~0u, bad & 1)) break;
    if (++it > (1u << 21)) __trap();
    __nanosleep(400);
  }
#pragma unroll
  for (int i = 0; i < N; i++) { v[0] += bf_lo(a[i].x); v[1] += bf_hi(a[i].x); v[2] += bf_lo(a[i].y); v[3] += bf_hi(a[i].y); }
}
__device__ __forceinline__ void reduce_atom8(const Params& p, int m, int j, int w) {
  mbar_wait_slow(BAR_P1, 0);
  const uint32_t par = get_par();
#pragma unroll 1
  for (int c = w; c < 8; c += 3) {
    const uint2* src = reinterpret_cast<const uint2*>(part_ptr(m, 8, 0) + j * 128 + (c >> 1) * 32) + (c & 1);
    const size_t off = (size_t)(m * 128 + j * 16) * DM + 512 + 8 * c;
    float v[4] = {0.f, 0.f, 0.f, 0.f};
    sum_pieces<5>(v, src, par);
    uint32_t x0, x1;
    {
      const int l = who().lane();
      const uint32_t* xp = reinterpret_cast<const uint32_t*>(p.xg + off) + (l >> 2) * (DM / 2) + (l & 3);
      asm volatile("ld.global.nc.b32 %0, [%2];\nld.global.nc.b32 %1, [%2+9216];" : "=r"(x0), "=r"(x1) : "l"(xp));
    }
    sum_pieces<4>(v, src + 5 * 2048, par);
    const int l = who().lane();
    const uint32_t d2 = lds32(OFF_DSK + 128 + c * 16 + (l & 3) * 4), sa = OFF_STATS + (j * 16 + (l >> 2)) * 8;
    float a, b;
    row_stat(lds64(sa)).resid(a, b, x0, d2);
    v[0] += a; v[1] += b;
    row_stat(lds64(sa + 64)).resid(a, b, x1, d2);
    float2* o = reinterpret_cast<float2*>(p.out + off) + (l >> 2) * (DM / 2) + (l & 3);
    __stcs(o, make_float2(v[0], v[1]));
    __stcs(o + 4 * DM, make_float2(v[2] + a, v[3] + b));
  }
}
__device__ __forceinline__ void prefetch_weights(const Params& p, int m, int j) {
  mbar_wait_b(BAR_X + 5 * 8, 0);
#pragma unroll 1
  for (int n = m; n < 162; n += 16) {
    tma_prefetch((n & 1) ? &p.wu : &p.wg, DM * j + 64 * (n / 18), 64 * ((n % 18) >> 1));
    __nanosleep(500);
  }
#pragma unroll 1
  for (int n = m; n < 101; n += 16) {
    const int a = n / 11;
    int c0, c1;
    const CUtensorMap* mp = p2_box(p, n < 99 ? j : 8, n < 99 ? n % 11 : n - 90, n >= 99 ? j : a ? (j + a) & 7 : 8, c0, c1);
    tma_prefetch(mp, c0, c1);
    __nanosleep(1000);
  }
}

__global__ void __launch_bounds__(NTHREADS, 1) fused_kernel(const __grid_constant__ Params p) {
  extern __shared__ __align__(1024) uint8_t smem[];
  const int tid = threadIdx.x, lane = tid & 31, b = blockIdx.x;
  const bool spare = b >= 128;
  const int m = spare ? b - 128 : b >> 3, j = b & 7;
  if (tid < 256) {
    asm volatile("setmaxnreg.inc.sync.aligned.u32 240;");
    consumer(p, spare, m, j);
  } else {
    asm volatile("setmaxnreg.dec.sync.aligned.u32 24;");
    if (__shfl_sync(~0u, tid >> 5, 0) == 8) {
      if (lane == 0) {
#pragma unroll
        for (int i = 0; i < 6; i++) mbar_init(BAR_X + i * 8, 1);
        fence_init();
      }
      __syncwarp();
      load_x(p, m, 0, 0, 3);
    } else if (tid == 288) {
#pragma unroll
      for (int i = 0; i < 14; i++) mbar_init(BAR_FULL + i * 8, 1);
      fence_init();
    } else if (tid == 320) {
#pragma unroll
      for (int i = 0; i < 14; i++) mbar_init(BAR_EMPTY + i * 8, 8);
      fence_init();
    } else if (tid == 352) {
      if ((uint32_t)__cvta_generic_to_shared(smem) != sb) __trap();
      mbar_init(BAR_STASH, 8); mbar_init(BAR_P1, 8); mbar_init(BAR_SCAN, spare ? 8 : 2); mbar_init(BAR_G8, 1); mbar_init(BAR_PAR, 1); mbar_init(BAR_DONE, 8);
      fence_init();
    }
    bar_sync(0, 128);
    const int aw = __shfl_sync(~0u, who().w8(), 0);
    if (aw == 10) bar_arrive(6, 288);
    if (aw == 8) {
      if (!spare) producer_main(p, b >> 3, j); else producer_spare(p, b & 3);
    } else if (aw < 11) {
      if (!spare) {
        scan_worker(p, b >> 3, j, tid - 288);
        reduce_atom8(p, b >> 3, j, __shfl_sync(~0u, who().w8(), 0) - 9);
      } else if (tid == 288) {
#pragma unroll 1
        for (int r = 0; r < 4; r++) {
          mbar_wait_b(BAR_SCAN, r & 1);
          asm volatile("st.release.gpu.global.b32 [%0], %1;" ::"l"(g_flag + (b & 3) + 4 * r), "r"(get_par()) : "memory");
        }
      }
    } else {
      const uint32_t ep = g_epoch[b] + 1;
      const uint32_t d = reinterpret_cast<const uint32_t*>(p.dskip)[32 * j + lane], d8 = reinterpret_cast<const uint32_t*>(p.dskip)[256 + lane];
      if (b < 80) tma_prefetch((b & 8) ? &p.bim : &p.bre, 64 * (4 + (b >> 4)), 64 * j);
      if (lane < 10) asm volatile("prefetch.tensormap [%0];" ::"l"(&p.x + lane) : "memory");
      if (lane == 0) sts32(OFF_PAR, ep & 1);
      sts32(OFF_DSK + (lane & 24) * 4 + (lane & 3) * 8 + (lane & 4), hadd2(d, d)); sts32(OFF_DSK + 128 + lane * 4, hadd2(d8, d8));
      __syncwarp();
      if (lane == 0) { mbar_arrive(BAR_PAR); if (spare) g_epoch[b] = ep; }
      __syncwarp();
      if (!spare) {
        prefetch_weights(p, b >> 3, j);
        mbar_wait_slow(BAR_P1, 0);
        if (lane == 0) g_epoch[b] = ep;
        uint32_t f, it = 0;
        while (true) {
          asm volatile("ld.acquire.gpu.global.b32 %0, [%1];" : "=r"(f) : "l"(g_flag + (b >> 3)) : "memory");
          if (f == (ep & 1)) break;
          if (++it > (1u << 21)) __trap();
          __nanosleep(300);
        }
        fence_async_all();
        mbar_arrive_w(BAR_G8);
        reduce_atom8(p, b >> 3, j, 2);
      }
      if (lane == 0) mbar_wait_b(BAR_DONE, 0);
      __syncwarp();
    }
  }
}

typedef CUresult (*EncodeFn)(CUtensorMap*, CUtensorMapDataType, cuuint32_t, void*, const cuuint64_t*, const cuuint64_t*, const cuuint32_t*,
                             const cuuint32_t*, CUtensorMapInterleave, CUtensorMapSwizzle, CUtensorMapL2promotion, CUtensorMapFloatOOBfill);

void make_map(EncodeFn fn, CUtensorMap* map, const void* ptr, int rows, int cols, int box_rows = 64, int kblocks = 0) {
  cuuint64_t dims[3] = {(cuuint64_t)(kblocks ? 64 : cols), (cuuint64_t)rows, (cuuint64_t)(cols / 64)}, strides[2] = {(cuuint64_t)cols * 2, 128};
  cuuint32_t box[3] = {64, (cuuint32_t)box_rows, (cuuint32_t)kblocks}, es[3] = {1, 1, 1};
  fn(map, CU_TENSOR_MAP_DATA_TYPE_BFLOAT16, kblocks ? 3 : 2, const_cast<void*>(ptr), dims, strides, box, es, CU_TENSOR_MAP_INTERLEAVE_NONE,
     CU_TENSOR_MAP_SWIZZLE_128B, CU_TENSOR_MAP_L2_PROMOTION_L2_128B, CU_TENSOR_MAP_FLOAT_OOB_FILL_NONE);
}

struct Win { int pair, from, until; };
struct RingSim {
  int rel[14] = {0}, uses[14] = {0}, last[14];
  RingSim() { for (int i = 0; i < 14; i++) last[i] = -100 + i; }
  uint32_t take(int pr, int i) {
    const int n = rel[pr];
    const uint32_t e = pair_e(pr) | ((uint32_t)(uses[pr] & 1) << 31) | (n == 0 ? 0x8000u : ((uint32_t)((n - 1) & 1) << 30));
    uses[pr]++; rel[pr]++; last[pr] = i;
    return e;
  }
  uint32_t next(const Win* win, int nwin, int i) {
    int best = -1;
    for (int w = 0; w < nwin; w++) {
      if (i == win[w].from && win[w].pair < 10) rel[win[w].pair]++;
      if (i >= win[w].from && i <= win[w].until && (best < 0 || last[win[w].pair] < last[best])) best = win[w].pair;
    }
    return take(best, i);
  }
};
void make_schedule(Params& p) {
  const Win win[] = {
    {10, 0, 999}, {11, 0, 999}, {12, 0, 999}, {13, 0, 999}, {4, 4, 999}, {9, 7, 999},
    {2, 4, 32}, {7, 7, 32},
    {1, 96, 999}, {6, 96, 999},
    {1, 4, 50}, {6, 7, 50},
  };
  RingSim r;
  for (int i = 0; i < NSLOT; i++) {
    p.sched[i] = r.next(win, sizeof(win) / sizeof(win[0]), i);
    if (i >= 17 && i < 89 && (i - 17) % 9 == 0)
      for (int w = 0, t = (i - 17) / 9; w < 2; w++) {
        const int pr = w * 5 + (7 - t) / 2;
        p.reclaim[w][t] = r.uses[pr] > 0 ? pair_e(pr) | ((uint32_t)((r.rel[pr] - 1) & 1) << 31) : 0;
      }
  }
  for (int w = 0; w < 2; w++) { r.rel[5 * w]++; p.sched[NSLOT + w] = r.take(5 * w, NSLOT); }
  Win ws[28] = {{10, 0, 999}, {11, 0, 999}, {12, 0, 999}, {13, 0, 999}};
  for (int k = 0; k < 24; k++) ws[4 + k] = Win{(k & 1) * 5 + (k % 6 < 2 ? 1 : k % 6 < 4 ? 2 : 4), (k < 6 ? 4 : 12 * (k / 6) + 1), (k < 6 ? 8 : 12 * (k / 6) + 5)};
  RingSim q;
  for (int i = 0; i < NSLOT_SP; i++) p.sched_sp[i] = q.next(ws, 28, i);
}

}

extern "C" void kernel_launch(void* const* d_in, const int* in_sizes, int n_in, void* d_out, int out_size) {
  static EncodeFn fn = nullptr;
  static void* hs = nullptr;
  if (!fn) {
    void* f = nullptr;
    cudaDriverEntryPointQueryResult qr;
    cudaGetDriverEntryPoint("cuTensorMapEncodeTiled", &f, cudaEnableDefault, &qr);
    fn = (EncodeFn)f;
    cudaGetSymbolAddress(&hs, g_hs);
    cudaFuncSetAttribute(fused_kernel, cudaFuncAttributeMaxDynamicSharedMemorySize, SMEM_BYTES);
  }
  Params p;
  make_map(fn, &p.x, d_in[0], SEQ, DM, 64, 3);
  make_map(fn, &p.x2, d_in[0], SEQ, DM, 128);
  make_map(fn, &p.bre, d_in[3], DM, DM);
  make_map(fn, &p.bim, d_in[4], DM, DM);
  make_map(fn, &p.cre, d_in[5], DM, DM);
  make_map(fn, &p.cim, d_in[6], DM, DM);
  make_map(fn, &p.wg, d_in[10], DM, FF);
  make_map(fn, &p.wu, d_in[11], DM, FF);
  make_map(fn, &p.wd, d_in[12], FF, DM);
  make_map(fn, &p.hs, hs, SEQ, 1152);
  p.xg = (const __nv_bfloat16*)d_in[0];
  p.lam_re = (const __nv_bfloat16*)d_in[1];
  p.lam_im = (const __nv_bfloat16*)d_in[2];
  p.log_dt = (const __nv_bfloat16*)d_in[7];
  p.dskip = (const __nv_bfloat16*)d_in[8];
  p.out = (float*)d_out;
  p.zero = 0;
  make_schedule(p);
  fused_kernel<<<132, NTHREADS, SMEM_BYTES>>>(p);
}
```

```cpp
#include <cuda_runtime.h>
#include <cuda_bf16.h>
#include <cuda.h>
#include <stdint.h>

namespace {

constexpr int SEQ = 2048, DM = 576, FF = 4608;
constexpr uint32_t UNIT = 8192, WREG = 10 * UNIT;
constexpr int NSLOT = 144, NSLOT_SP = 48;
constexpr int SMEM_BYTES = 232448;
constexpr uint32_t sb = 1024;
constexpr uint32_t OFF_STATS = sb + 28 * UNIT;
constexpr uint32_t OFF_DSK = OFF_STATS + 1024;
constexpr uint32_t BAR_FULL = OFF_DSK + 256;
constexpr uint32_t BAR_EMPTY = BAR_FULL + 14 * 8;
constexpr uint32_t BAR_X = BAR_EMPTY + 14 * 8;
constexpr uint32_t BAR_STASH = BAR_X + 6 * 8;
constexpr uint32_t BAR_P1 = BAR_STASH + 8;
constexpr uint32_t BAR_SCAN = BAR_P1 + 8;
constexpr uint32_t BAR_G8 = BAR_SCAN + 8;
constexpr uint32_t BAR_PAR = BAR_G8 + 8;
constexpr uint32_t BAR_DONE = BAR_PAR + 8;
constexpr uint32_t OFF_PAR = BAR_DONE + 8;
constexpr int NTHREADS = 384;
constexpr int SKEW = 4, SKEW2 = 2;
#define MAPB 1
#define XPRI 0
#define XAT 1
constexpr int AHEAD = 3;

struct Params {
  CUtensorMap x, x2, wg, wu, wd, bre, bim, cre, cim, hs;
  const __nv_bfloat16 *xg, *lam_re, *lam_im, *log_dt, *dskip;
  float* out;
  uint32_t zero;
  uint32_t sched[NSLOT + 2];
  uint32_t sched_sp[NSLOT_SP];
  uint32_t reclaim[2][8];
};

__device__ uint4 g_part[16 * 9 * 9 * 1024];
__device__ uint2 g_state[9 * 16 * 64];
__device__ uint2 g_stats[SEQ];
__device__ __nv_bfloat16 g_hs[SEQ * 1152];
__device__ uint32_t g_flag[16];
__device__ uint32_t g_epoch[132];
#define PCLK "%%globaltimer_lo"
#define PROBE(w, n)
#define CPROBE(n)
#define PROF_DUMP()
#define TR(slot, k)

__device__ __forceinline__ void mbar_init(uint32_t bar, uint32_t cnt) { asm volatile("mbarrier.init.shared::cta.b64 [%0], %1;" ::"r"(bar), "r"(cnt) : "memory"); }
__device__ __forceinline__ void mbar_expect_tx(uint32_t bar, uint32_t bytes) { asm volatile("{\n.reg .pred p;\nelect.sync _|p, 0xffffffff;\n@p mbarrier.arrive.expect_tx.shared::cta.b64 _, [%0], %1;\n}" ::"r"(bar), "r"(bytes) : "memory"); }
__device__ __forceinline__ void mbar_arrive(uint32_t bar) { asm volatile("mbarrier.arrive.shared::cta.b64 _, [%0];" ::"r"(bar) : "memory"); }
__device__ __forceinline__ void mbar_arrive_w(uint32_t bar) {
  asm volatile("{\n.reg .pred p;\nelect.sync _|p, 0xffffffff;\n@p mbarrier.arrive.shared::cta.b64 _, [%0];\n}" ::"r"(bar) : "memory");
}
__device__ __forceinline__ void mbar_wait(uint32_t bar, uint32_t parity) {
  asm volatile("{\n.reg .pred p;\nLOOP:\nmbarrier.try_wait.parity.shared::cta.b64 p, [%0], %1;\n@!p bra LOOP;\n}" ::"r"(bar), "r"(parity) : "memory");
}
__device__ __forceinline__ void mbar_wait_b(uint32_t bar, uint32_t parity) {
  asm volatile(
      "{\n.reg .pred p;\n.reg .u32 c;\nmov.u32 c, 0;\n"
      "LOOP:\nmbarrier.try_wait.parity.shared::cta.b64 p, [%0], %1;\n@p bra DONE;\n"
      "add.u32 c, c, 1;\nsetp.lt.u32 p, c, 0x400000;\n@p bra LOOP;\ntrap;\nDONE:\n}" ::"r"(bar), "r"(parity) : "memory");
}
__device__ __forceinline__ void mbar_wait_slow(uint32_t bar, uint32_t parity) {
  asm volatile(
      "{\n.reg .pred p;\n.reg .u32 c;\nmov.u32 c, 0;\n"
      "LOOP:\nmbarrier.test_wait.parity.shared::cta.b64 p, [%0], %1;\n@p bra DONE;\nnanosleep.u32 256;\n"
      "add.u32 c, c, 1;\nsetp.lt.u32 p, c, 0x400000;\n@p bra LOOP;\ntrap;\nDONE:\n}" ::"r"(bar), "r"(parity) : "memory");
}
__device__ __forceinline__ void tma_load(uint32_t dst, const CUtensorMap* map, int c0, int c1, uint32_t bar) {
  asm volatile("{\n.reg .pred p;\nelect.sync _|p, 0xffffffff;\n"
               "@p cp.async.bulk.tensor.2d.shared::cluster.global.mbarrier::complete_tx::bytes [%0], [%1, {%3, %4}], [%2];\n}"
               ::"r"(dst), "l"(map), "r"(bar), "r"(c0), "r"(c1) : "memory");
}
__device__ __forceinline__ void tma_load3(uint32_t dst, const CUtensorMap* map, int c0, int c1, int c2, uint32_t bar) {
  asm volatile("{\n.reg .pred p;\nelect.sync _|p, 0xffffffff;\n"
               "@p cp.async.bulk.tensor.3d.shared::cluster.global.mbarrier::complete_tx::bytes [%0], [%1, {%3, %4, %5}], [%2];\n}"
               ::"r"(dst), "l"(map), "r"(bar), "r"(c0), "r"(c1), "r"(c2) : "memory");
}
__device__ __forceinline__ void tma_prefetch(const CUtensorMap* map, int c0, int c1) {
  asm volatile("{\n.reg .pred p;\nelect.sync _|p, 0xffffffff;\n@p cp.async.bulk.prefetch.tensor.2d.L2.global [%0, {%1, %2}];\n}" ::"l"(map), "r"(c0), "r"(c1) : "memory");
}
__device__ __forceinline__ void fence_async() { asm volatile("fence.proxy.async.shared::cta;" ::: "memory"); }
__device__ __forceinline__ void fence_init() { asm volatile("fence.mbarrier_init.release.cluster;" ::: "memory"); }
__device__ __forceinline__ void fence_async_all() { asm volatile("fence.proxy.async;" ::: "memory"); }
__device__ __forceinline__ void bar_sync(int id, int n) { asm volatile("bar.sync %0, %1;" ::"r"(id), "r"(n) : "memory"); }
__device__ __forceinline__ void bar_arrive(int id, int n) { asm volatile("bar.arrive %0, %1;" ::"r"(id), "r"(n) : "memory"); }
__device__ __forceinline__ void wg_fence() { asm volatile("wgmma.fence.sync.aligned;" ::: "memory"); }
__device__ __forceinline__ void wg_commit() { asm volatile("wgmma.commit_group.sync.aligned;" ::: "memory"); }
template <int N> __device__ __forceinline__ void wg_wait() { asm volatile("wgmma.wait_group.sync.aligned %0;" ::"n"(N) : "memory"); }
template <int N> __device__ __forceinline__ void fence_regs(float (&a)[N]) {
#pragma unroll
  for (int i = 0; i < N; i++) asm volatile("" : "+f"(a[i])::"memory");
}
__device__ __forceinline__ void ldsm4(uint32_t* r, uint32_t addr) {
  asm volatile("ldmatrix.sync.aligned.m8n8.x4.shared.b16 {%0,%1,%2,%3}, [%4];" : "=r"(r[0]), "=r"(r[1]), "=r"(r[2]), "=r"(r[3]) : "r"(addr) : "memory");
}
__device__ __forceinline__ void stsm4(uint32_t addr, const uint32_t* r) {
  asm volatile("stmatrix.sync.aligned.m8n8.x4.shared.b16 [%0], {%1,%2,%3,%4};" ::"r"(addr), "r"(r[0]), "r"(r[1]), "r"(r[2]), "r"(r[3]) : "memory");
}
__device__ __forceinline__ void sts32(uint32_t addr, uint32_t a) { asm volatile("st.shared.b32 [%0], %1;" ::"r"(addr), "r"(a) : "memory"); }
__device__ __forceinline__ void sts64(uint32_t addr, uint32_t a, uint32_t b) { asm volatile("st.shared.v2.b32 [%0], {%1,%2};" ::"r"(addr), "r"(a), "r"(b) : "memory"); }
__device__ __forceinline__ uint32_t lds32(uint32_t addr) { uint32_t v; asm volatile("ld.shared.b32 %0, [%1];" : "=r"(v) : "r"(addr) : "memory"); return v; }
__device__ __forceinline__ uint2 lds64(uint32_t addr) { uint2 v; asm volatile("ld.shared.v2.b32 {%0,%1}, [%2];" : "=r"(v.x), "=r"(v.y) : "r"(addr) : "memory"); return v; }
__device__ __forceinline__ float2 lds64f(uint32_t addr) { float2 v; asm volatile("ld.shared.v2.f32 {%0,%1}, [%2];" : "=f"(v.x), "=f"(v.y) : "r"(addr) : "memory"); return v; }
__device__ __forceinline__ void ld_tag16(uint32_t* r, const uint4* p) {
  asm volatile("{\n.reg .b128 t;\nld.relaxed.gpu.global.b128 t, [%4];\nmov.b128 {%0,%1,%2,%3}, t;\n}" : "=r"(r[0]), "=r"(r[1]), "=r"(r[2]), "=r"(r[3]) : "l"(p) : "memory");
}
__device__ __forceinline__ uint2 ld_tag8(const uint2* p) {
  uint2 r;
  asm volatile("{\n.reg .b64 t;\nld.relaxed.gpu.global.b64 t, [%2];\nmov.b64 {%0,%1}, t;\n}" : "=r"(r.x), "=r"(r.y) : "l"(p) : "memory");
  return r;
}
__device__ __forceinline__ void st_tag16(uint4* p, const uint32_t* r) {
  asm volatile("{\n.reg .b128 t;\nmov.b128 t, {%1,%2,%3,%4};\nst.relaxed.gpu.global.b128 [%0], t;\n}" ::"l"(p), "r"(r[0]), "r"(r[1]), "r"(r[2]), "r"(r[3]) : "memory");
}
__device__ __forceinline__ void st_tag8(uint2* p, uint32_t a, uint32_t b) {
  asm volatile("{\n.reg .b64 t;\nmov.b64 t, {%1,%2};\nst.relaxed.gpu.global.b64 [%0], t;\n}" ::"l"(p), "r"(a), "r"(b) : "memory");
}
__device__ __forceinline__ uint32_t pack2(float lo, float hi) { uint32_t r; asm("cvt.rn.bf16x2.f32 %0, %1, %2;" : "=r"(r) : "f"(hi), "f"(lo)); return r; }
__device__ __forceinline__ float bf_lo(uint32_t v) { return __uint_as_float(v << 16); }
__device__ __forceinline__ float bf_hi(uint32_t v) { return __uint_as_float(v & 0xffff0000u); }
__device__ __forceinline__ float bf_round(float v) { return __bfloat162float(__float2bfloat16_rn(v)); }
__device__ __forceinline__ uint32_t hsub2(uint32_t a, uint32_t b) { uint32_t r; asm("sub.rn.bf16x2 %0, %1, %2;" : "=r"(r) : "r"(a), "r"(b)); return r; }
__device__ __forceinline__ uint32_t hmul2(uint32_t a, uint32_t b) { uint32_t r; asm("mul.rn.bf16x2 %0, %1, %2;" : "=r"(r) : "r"(a), "r"(b)); return r; }
__device__ __forceinline__ uint32_t hadd2(uint32_t a, uint32_t b) { uint32_t r; asm("add.rn.bf16x2 %0, %1, %2;" : "=r"(r) : "r"(a), "r"(b)); return r; }
__device__ __forceinline__ uint32_t hfma2(uint32_t a, uint32_t b, uint32_t c) { uint32_t r; asm("fma.rn.bf16x2 %0, %1, %2, %3;" : "=r"(r) : "r"(a), "r"(b), "r"(c)); return r; }
__device__ __forceinline__ float sqrt_hw(float x) { float r; asm("sqrt.approx.f32 %0, %1;" : "=f"(r) : "f"(x)); return r; }
__device__ __forceinline__ float tanh_hw(float x) { float r; asm("tanh.approx.f32 %0, %1;" : "=f"(r) : "f"(x)); return r; }
__device__ __forceinline__ uint32_t get_par() { mbar_wait(BAR_PAR, 0); return lds32(OFF_PAR); }

__device__ __forceinline__ uint64_t desc_k(uint32_t a16) { return 0x4000004000000000ull | ((a16 & 0x3fff) | (1u << 16)); }
__device__ __forceinline__ uint64_t desc_mn(uint32_t a16) { return 0x4000004000000000ull | ((a16 & 0x3fff) | ((8192u >> 4) << 16)); }
__host__ __device__ constexpr uint32_t pair_e(int pair) { return (sb + pair * 2 * UNIT) >> 4; }
__device__ __forceinline__ uint32_t bar_of(uint32_t e) { return (e >> 7) & 0x78; }
__device__ __forceinline__ uint32_t addr_of(uint32_t e) { return (e & 0x3fff) << 4; }

template <int TB> __device__ __forceinline__ void wgmma_rs_n128(float (&d)[64], const uint32_t* a, uint64_t db, int ob, int sd) {
  asm volatile("{\n.reg .pred p;\n.reg .b64 b;\nsetp.ne.b32 p, %70, 0;\nadd.u64 b, %68, %69;\n"
    "wgmma.mma_async.sync.aligned.m64n128k16.f32.bf16.bf16 {%0,%1,%2,%3,%4,%5,%6,%7,%8,%9,%10,%11,%12,%13,%14,%15,%16,%17,%18,%19,%20,%21,%22,%23,%24,%25,%26,%27,%28,%29,%30,%31,%32,%33,%34,%35,%36,%37,%38,%39,%40,%41,%42,%43,%44,%45,%46,%47,%48,%49,%50,%51,%52,%53,%54,%55,%56,%57,%58,%59,%60,%61,%62,%63}, "
    "{%64,%65,%66,%67}, b, p, 1, 1, %71;\n}"
    : "+f"(d[0]),"+f"(d[1]),"+f"(d[2]),"+f"(d[3]),"+f"(d[4]),"+f"(d[5]),"+f"(d[6]),"+f"(d[7]),"+f"(d[8]),"+f"(d[9]),"+f"(d[10]),"+f"(d[11]),"+f"(d[12]),"+f"(d[13]),"+f"(d[14]),"+f"(d[15]),"+f"(d[16]),"+f"(d[17]),"+f"(d[18]),"+f"(d[19]),"+f"(d[20]),"+f"(d[21]),"+f"(d[22]),"+f"(d[23]),"+f"(d[24]),"+f"(d[25]),"+f"(d[26]),"+f"(d[27]),"+f"(d[28]),"+f"(d[29]),"+f"(d[30]),"+f"(d[31]),"+f"(d[32]),"+f"(d[33]),"+f"(d[34]),"+f"(d[35]),"+f"(d[36]),"+f"(d[37]),"+f"(d[38]),"+f"(d[39]),"+f"(d[40]),"+f"(d[41]),"+f"(d[42]),"+f"(d[43]),"+f"(d[44]),"+f"(d[45]),"+f"(d[46]),"+f"(d[47]),"+f"(d[48]),"+f"(d[49]),"+f"(d[50]),"+f"(d[51]),"+f"(d[52]),"+f"(d[53]),"+f"(d[54]),"+f"(d[55]),"+f"(d[56]),"+f"(d[57]),"+f"(d[58]),"+f"(d[59]),"+f"(d[60]),"+f"(d[61]),"+f"(d[62]),"+f"(d[63])
    : "r"(a[0]), "r"(a[1]), "r"(a[2]), "r"(a[3]), "l"(db), "l"((uint64_t)ob), "r"(sd), "n"(TB));
}
template <int TB> __device__ __forceinline__ void wgmma_ss_n128(float (&d)[64], uint64_t da, int oa, uint64_t db, int ob, int sd) {
  asm volatile("{\n.reg .pred p;\n.reg .b64 a, b;\nsetp.ne.b32 p, %68, 0;\nadd.u64 a, %64, %65;\nadd.u64 b, %66, %67;\n"
    "wgmma.mma_async.sync.aligned.m64n128k16.f32.bf16.bf16 {%0,%1,%2,%3,%4,%5,%6,%7,%8,%9,%10,%11,%12,%13,%14,%15,%16,%17,%18,%19,%20,%21,%22,%23,%24,%25,%26,%27,%28,%29,%30,%31,%32,%33,%34,%35,%36,%37,%38,%39,%40,%41,%42,%43,%44,%45,%46,%47,%48,%49,%50,%51,%52,%53,%54,%55,%56,%57,%58,%59,%60,%61,%62,%63}, "
    "a, b, p, 1, 1, 0, %69;\n}"
    : "+f"(d[0]),"+f"(d[1]),"+f"(d[2]),"+f"(d[3]),"+f"(d[4]),"+f"(d[5]),"+f"(d[6]),"+f"(d[7]),"+f"(d[8]),"+f"(d[9]),"+f"(d[10]),"+f"(d[11]),"+f"(d[12]),"+f"(d[13]),"+f"(d[14]),"+f"(d[15]),"+f"(d[16]),"+f"(d[17]),"+f"(d[18]),"+f"(d[19]),"+f"(d[20]),"+f"(d[21]),"+f"(d[22]),"+f"(d[23]),"+f"(d[24]),"+f"(d[25]),"+f"(d[26]),"+f"(d[27]),"+f"(d[28]),"+f"(d[29]),"+f"(d[30]),"+f"(d[31]),"+f"(d[32]),"+f"(d[33]),"+f"(d[34]),"+f"(d[35]),"+f"(d[36]),"+f"(d[37]),"+f"(d[38]),"+f"(d[39]),"+f"(d[40]),"+f"(d[41]),"+f"(d[42]),"+f"(d[43]),"+f"(d[44]),"+f"(d[45]),"+f"(d[46]),"+f"(d[47]),"+f"(d[48]),"+f"(d[49]),"+f"(d[50]),"+f"(d[51]),"+f"(d[52]),"+f"(d[53]),"+f"(d[54]),"+f"(d[55]),"+f"(d[56]),"+f"(d[57]),"+f"(d[58]),"+f"(d[59]),"+f"(d[60]),"+f"(d[61]),"+f"(d[62]),"+f"(d[63])
    : "l"(da), "l"((uint64_t)oa), "l"(db), "l"((uint64_t)ob), "r"(sd), "n"(TB));
}
template <int TB> __device__ __forceinline__ void wgmma_rs_n64(float (&d)[32], const uint32_t* a, uint64_t db, int ob, int sd) {
  asm volatile("{\n.reg .pred p;\n.reg .b64 b;\nsetp.ne.b32 p, %38, 0;\nadd.u64 b, %36, %37;\n"
    "wgmma.mma_async.sync.aligned.m64n64k16.f32.bf16.bf16 {%0,%1,%2,%3,%4,%5,%6,%7,%8,%9,%10,%11,%12,%13,%14,%15,%16,%17,%18,%19,%20,%21,%22,%23,%24,%25,%26,%27,%28,%29,%30,%31}, "
    "{%32,%33,%34,%35}, b, p, 1, 1, %39;\n}"
    : "+f"(d[0]),"+f"(d[1]),"+f"(d[2]),"+f"(d[3]),"+f"(d[4]),"+f"(d[5]),"+f"(d[6]),"+f"(d[7]),"+f"(d[8]),"+f"(d[9]),"+f"(d[10]),"+f"(d[11]),"+f"(d[12]),"+f"(d[13]),"+f"(d[14]),"+f"(d[15]),"+f"(d[16]),"+f"(d[17]),"+f"(d[18]),"+f"(d[19]),"+f"(d[20]),"+f"(d[21]),"+f"(d[22]),"+f"(d[23]),"+f"(d[24]),"+f"(d[25]),"+f"(d[26]),"+f"(d[27]),"+f"(d[28]),"+f"(d[29]),"+f"(d[30]),"+f"(d[31])
    : "r"(a[0]), "r"(a[1]), "r"(a[2]), "r"(a[3]), "l"(db), "l"((uint64_t)ob), "r"(sd), "n"(TB));
}
template <int TB> __device__ __forceinline__ void wgmma_ss_n64(float (&d)[32], uint64_t da, int oa, uint64_t db, int ob, int sd) {
  asm volatile("{\n.reg .pred p;\n.reg .b64 a, b;\nsetp.ne.b32 p, %36, 0;\nadd.u64 a, %32, %33;\nadd.u64 b, %34, %35;\n"
    "wgmma.mma_async.sync.aligned.m64n64k16.f32.bf16.bf16 {%0,%1,%2,%3,%4,%5,%6,%7,%8,%9,%10,%11,%12,%13,%14,%15,%16,%17,%18,%19,%20,%21,%22,%23,%24,%25,%26,%27,%28,%29,%30,%31}, "
    "a, b, p, 1, 1, 0, %37;\n}"
    : "+f"(d[0]),"+f"(d[1]),"+f"(d[2]),"+f"(d[3]),"+f"(d[4]),"+f"(d[5]),"+f"(d[6]),"+f"(d[7]),"+f"(d[8]),"+f"(d[9]),"+f"(d[10]),"+f"(d[11]),"+f"(d[12]),"+f"(d[13]),"+f"(d[14]),"+f"(d[15]),"+f"(d[16]),"+f"(d[17]),"+f"(d[18]),"+f"(d[19]),"+f"(d[20]),"+f"(d[21]),"+f"(d[22]),"+f"(d[23]),"+f"(d[24]),"+f"(d[25]),"+f"(d[26]),"+f"(d[27]),"+f"(d[28]),"+f"(d[29]),"+f"(d[30]),"+f"(d[31])
    : "l"(da), "l"((uint64_t)oa), "l"(db), "l"((uint64_t)ob), "r"(sd), "n"(TB));
}

struct RowStat {
  uint32_t m2, rh, rl;
  __device__ __forceinline__ uint32_t norm_half(uint32_t x) const { uint32_t d = hsub2(x, m2); return hfma2(d, rh, hmul2(d, rl)); }
  __device__ __forceinline__ void resid(float& a, float& b, uint32_t x, uint32_t d2) const {
    uint32_t t = hmul2(norm_half(x), d2);
    a = bf_lo(x) + bf_lo(t); b = bf_hi(x) + bf_hi(t);
  }
};
__device__ __forceinline__ RowStat row_stat(uint2 s) { return RowStat{__byte_perm(s.x, 0, 0x1010), __byte_perm(s.x, 0, 0x3232), __byte_perm(s.y, 0, 0x1010)}; }
__device__ __forceinline__ uint2 encode_stat(float sum, float sumsq) {
  const float mean = sum * (1.f / DM), var = fmaxf(fmaf(-mean, mean, sumsq * (1.f / DM)), 0.f);
  const float r = __fdividef(0.5f, bf_round(sqrt_hw(bf_round(bf_round(var) + 1e-5f)))), rhi = bf_round(r);
  return make_uint2(pack2(mean, rhi), pack2(r - rhi, 0.f));
}
__device__ __forceinline__ void publish_stats(const __nv_bfloat16* x, int row, int lane) {
  const uint2* xp = reinterpret_cast<const uint2*>(x + (size_t)row * DM) + (lane & 15);
  const uint32_t par = (g_epoch[blockIdx.x] + 1) & 1;
  uint2 v[9];
#pragma unroll
  for (int i = 0; i < 9; i++) v[i] = __ldg(xp + 16 * i);
  float s = 0.f, q = 0.f;
#pragma unroll
  for (int i = 0; i < 9; i++) {
    const float a = bf_lo(v[i].x), b = bf_hi(v[i].x), c = bf_lo(v[i].y), d = bf_hi(v[i].y);
    s += (a + b) + (c + d);
    q += fmaf(a, a, b * b) + fmaf(c, c, d * d);
  }
#pragma unroll
  for (int o = 1; o < 16; o <<= 1) { s += __shfl_xor_sync(~0u, s, o); q += __shfl_xor_sync(~0u, q, o); }
  const uint2 st = encode_stat(s, q);
  if ((lane & 15) == 0) st_tag8(g_stats + row, st.x, st.y | (par << 16));
}
__device__ __forceinline__ uint32_t load_x_frags(uint32_t (&xa)[144], uint32_t (&n)[4], uint32_t fa, uint32_t bar, uint32_t xpar, uint32_t zero, const uint2* sp, int row, int lane) {
  uint32_t dep = 0;
  uint2 s0, s1;
#pragma unroll
  for (int g = 0; g < 3; g++) {
    mbar_wait(bar + g * 8, xpar);
    if (g == 2) { s0 = ld_tag8(sp); s1 = ld_tag8(sp + 8); }
#pragma unroll
    for (int i = 12 * g; i < 12 * g + 12; i++) ldsm4(&xa[4 * i], (fa ^ ((i & 3) << 5)) + (i >> 2) * UNIT);
#pragma unroll
    for (int i = 12 * g; i < 12 * g + 12; i++) dep |= xa[4 * i];
  }
  const uint32_t par = get_par();
  while (__any_sync(~0u, ((s0.y >> 16) != par) | ((s1.y >> 16) != par))) { s0 = ld_tag8(sp); s1 = ld_tag8(sp + 8); }
  if ((lane & 3) == 0) { sts64(OFF_STATS + row * 8, s0.x, s0.y); sts64(OFF_STATS + row * 8 + 64, s1.x, s1.y); }
  const float c0 = -bf_lo(s0.x) * bf_hi(s0.x), c1 = -bf_lo(s1.x) * bf_hi(s1.x);
  n[0] = __byte_perm(s0.x, 0, 0x3232); n[1] = pack2(c0, c0); n[2] = __byte_perm(s1.x, 0, 0x3232); n[3] = pack2(c1, c1);
  return dep & zero;
}
__device__ __forceinline__ void norm_blocks(uint32_t (&xa)[144], int b0, int b1, const uint32_t (&n)[4], uint32_t z) {
  const uint32_t c0 = n[1] ^ z, c1 = n[3] ^ z;
#pragma unroll
  for (int i = 16 * b0; i < 16 * b1; i += 2) { xa[i] = hfma2(xa[i], n[0], c0); xa[i + 1] = hfma2(xa[i + 1], n[2], c1); }
}

__device__ __forceinline__ uint32_t ring_get(uint32_t e, int tr) {
  TR(tr, 0);
  mbar_wait(BAR_FULL + bar_of(e), e >> 31);
  TR(tr, 1);
  return e;
}
__device__ __forceinline__ void ring_put(uint32_t e, uint32_t dep = 0) { mbar_arrive_w(BAR_EMPTY + bar_of(e) + dep); }
__device__ __forceinline__ void hand_over(int pair, uint32_t dep = 0) { mbar_arrive_w(BAR_EMPTY + pair * 8 + dep); }

template <int TB, class F>
__device__ __forceinline__ void tile_rs(float (&acc)[64], uint32_t (&xa)[144], const uint32_t* tab, int wg, int skew_bar, int s0, F shadow) {
  uint32_t prev = 0;
  if (wg == 1) bar_sync(skew_bar, 256);
#pragma unroll
  for (int kb = 0; kb < 9; kb++) {
    const uint32_t e = tab[kb], ba = ring_get(e, s0 + kb);
    const uint64_t db = TB ? desc_mn(ba) : desc_k(ba);
    wg_fence();
#pragma unroll
    for (int ks = 0; ks < 4; ks++) wgmma_rs_n128<TB>(acc, &xa[kb * 16 + ks * 4], db, TB ? ks * 128 : ks * 2, (kb | ks) != 0);
    wg_commit();
    if (kb == SKEW - 1 && wg == 0) bar_arrive(skew_bar, 256);
    shadow(kb);
    if (kb > 0) { wg_wait<1>(); TR(s0 + kb - 1, 2); ring_put(prev); }
    prev = e;
  }
  wg_wait<0>();
  TR(s0 + 8, 2);
  ring_put(prev);
  fence_regs(acc);
}
__device__ __forceinline__ uint32_t glu2(const float (&acc)[64], int i) {
  const float u0 = acc[32 + 2 * i], u1 = acc[33 + 2 * i];
  return pack2(fmaf(u0, tanh_hw(acc[2 * i]), u0), fmaf(u1, tanh_hw(acc[2 * i + 1]), u1));
}
__device__ __forceinline__ void stash_v(const float (&acc)[64], uint32_t wb, int row, int lane) {
  const uint32_t b = wb + (row & 63) * 256 + (lane & 3) * 8 + (lane & 12) * 8;
#pragma unroll
  for (int G = 0; G < 8; G++) {
    const uint32_t a = (b ^ ((G & 3) << 5)) + ((G & 4) << 5);
    sts64(a, pack2(acc[4 * G], acc[32 + 4 * G]), pack2(acc[4 * G + 1], acc[33 + 4 * G]));
    sts64(a + 8 * 256, pack2(acc[4 * G + 2], acc[34 + 4 * G]), pack2(acc[4 * G + 3], acc[35 + 4 * G]));
  }
}

__device__ __forceinline__ uint4* part_ptr(int m, int owner, int sender) { return g_part + (size_t)((m * 9 + owner) * 9 + sender) * 1024; }
template <int N>
__device__ __forceinline__ void pack_part(uint32_t* pk, const float (&a)[N], uint32_t par) {
#pragma unroll
  for (int i = 0; i < N / 2; i++) { pk[i] = pack2(a[2 * i], a[2 * i + 1]); if (!(i & 1)) pk[i] = (pk[i] & ~1u) | par; }
}
__device__ __forceinline__ void recv_issue(uint32_t* t, const uint4* src) {
#pragma unroll
  for (int i = 0; i < 4; i++) ld_tag16(&t[4 * i], src + i * 32);
}
__device__ __forceinline__ void recv_check(uint32_t* t, const uint4* src, uint32_t par) {
  while (__any_sync(~0u, ((t[0] ^ par) | (t[4] ^ par) | (t[8] ^ par) | (t[12] ^ par)) & 1)) recv_issue(t, src);
}
__device__ __forceinline__ void recv_add(float (&R)[32], const uint32_t* t, int i0, int i1) {
#pragma unroll
  for (int i = i0; i < i1; i++) { R[2 * i] += bf_lo(t[i]); R[2 * i + 1] += bf_hi(t[i]); }
}
__device__ __forceinline__ void store_out(const float (&R)[32], float* o, int lane) {
  o += (lane & 1) * 8 + (lane & 2) * 2;
  const bool odd = lane & 1;
#pragma unroll
  for (int i = 0; i < 8; i++) {
    const int k = (i >> 1) * 8 + (i & 1) * 2;
    const float r0 = __shfl_xor_sync(~0u, odd ? R[k] : R[k + 4], 1), r1 = __shfl_xor_sync(~0u, odd ? R[k + 1] : R[k + 5], 1);
    __stcs(reinterpret_cast<float4*>(o + (i >> 1) * 16 + (i & 1) * 8 * DM), odd ? make_float4(r0, r1, R[k + 4], R[k + 5]) : make_float4(R[k], R[k + 1], r0, r1));
  }
}
__device__ __forceinline__ void mma_g8(float (&acc)[32], uint32_t are, uint32_t aim, uint32_t cb) {
  wg_fence();
#pragma unroll
  for (int ks = 0; ks < 4; ks++) wgmma_ss_n64<0>(acc, desc_k(are), ks * 2, desc_k(cb), ks * 2, ks != 0);
#pragma unroll
  for (int ks = 0; ks < 4; ks++) wgmma_ss_n64<0>(acc, desc_k(aim), ks * 2, desc_k(cb), 512 + ks * 2, 1);
  wg_commit();
}

__device__ __forceinline__ float2 cmad(float2 a, float2 b, float2 c) {
  return make_float2(fmaf(a.x, b.x, fmaf(-a.y, b.y, c.x)), fmaf(a.x, b.y, fmaf(a.y, b.x, c.y)));
}
__device__ __forceinline__ float2 csq(float2 a) { return make_float2(fmaf(a.x, a.x, -a.y * a.y), 2.f * a.x * a.y); }
__device__ __forceinline__ void ssm_coef(const Params& p, int ch, float2& lam, float2& coef) {
  float a = __bfloat162float(p.lam_re[ch]), b = __bfloat162float(p.lam_im[ch]);
  float dt = bf_round(expf(__bfloat162float(p.log_dt[ch])));
  float e = expf(dt * a), sn, cs;
  sincospif(dt * b * 0.318309886183790672f, &sn, &cs);
  lam.x = e * cs; lam.y = e * sn;
  float nr = lam.x - 1.f, inv = __fdividef(4.f, a * a + b * b);
  coef.x = (nr * a + lam.y * b) * inv; coef.y = (lam.y * a - nr * b) * inv;
}
template <int NSEG>
__device__ __forceinline__ void ssm_scan(float2 lam, float2 coef, int c, int seg, int grp, int m, uint32_t par, uint32_t zero) {
  constexpr int TPW = 128 / NSEG, LB = NSEG > 1 ? 8 : 4;
  const int tb = seg * TPW;
  float2 s = {0.f, 0.f};
  uint32_t v[8], sa0 = sb + (tb >> 6) * WREG + (tb & 63) * 256 + c * 4;
  asm volatile("" : "+r"(sa0));
  uint32_t sa = sa0;
#pragma unroll
  for (int u = 0; u < 8; u++) v[u] = lds32((sa ^ ((u & 3) << 5)) + u * 256);
#pragma unroll 1
  for (int i = 0; i < TPW / 8; i++) {
    sa += (NSEG == 1 && i == 7) ? WREG - 7 * 2048 : 2048;
#pragma unroll
    for (int u = 0; u < 8; u++) {
      s = cmad(lam, s, make_float2(bf_lo(v[u]), bf_hi(v[u])));
      v[u] = lds32((sa ^ ((u & 3) << 5)) + u * 256);
    }
  }
  if (NSEG == 1 && c == 0) PROBE(2, 3);
  float2 pw = lam;
#pragma unroll 1
  for (int k = 1; k < TPW; k <<= 1) pw = csq(pw);
  const uint32_t xch = sb + 9 * UNIT + c * 8;
  if (NSEG > 1) {
    sts64(xch + seg * 512, __float_as_uint(s.x), __float_as_uint(s.y));
    bar_sync(5, 256);
    if (seg == NSEG - 1) {
      s = make_float2(0.f, 0.f);
#pragma unroll 1
      for (int w = 0; w < NSEG; w++) s = cmad(pw, s, lds64f(xch + w * 512));
    }
  }
  uint2* st = g_state + grp * 16 * 64 + c;
  if (seg == NSEG - 1) st_tag8(st + m * 64, (__float_as_uint(s.x) & ~1u) | par, __float_as_uint(s.y));
  float2 pl = pw;
#pragma unroll 1
  for (int k = TPW; k < 128; k <<= 1) pl = csq(pl);
  s = make_float2(0.f, 0.f);
#pragma unroll 1
  for (int k = m; k > 0; k -= LB, st += LB * 64) {
    uint2 a[LB];
    uint32_t it = 0, bad;
    do {
      if (++it > (1u << 21)) __trap();
      bad = 0;
#pragma unroll
      for (int i = 0; i < LB; i++) { a[i].x = par; if (i < k) a[i] = ld_tag8(st + i * 64); }
#pragma unroll
      for (int i = 0; i < LB; i++) bad |= a[i].x ^ par;
    } while (__any_sync(~0u, bad & 1));
#pragma unroll
    for (int i = 0; i < LB; i++)
      if (i < k) s = cmad(pl, s, make_float2(__uint_as_float(a[i].x), __uint_as_float(a[i].y)));
  }
  if (NSEG > 1) {
#pragma unroll 1
    for (int w = 0; w < seg; w++) s = cmad(pw, s, lds64f(xch + w * 512));
  }
  if (NSEG == 1 && c == 0) PROBE(2, 4);
  sa = sa0;
  uint32_t* hg = reinterpret_cast<uint32_t*>(g_hs + (size_t)(m * 128 + tb) * 1152 + grp * 128) + ((sa0 & 255) >> 3) + (sa0 & 4) * 8;
  const uint32_t sel = (sa0 & 4) ? 0x3276 : 0x5410;
#pragma unroll
  for (int u = 0; u < 4; u++) v[u] = lds32((sa ^ (u << 5)) + u * 256);
#pragma unroll 1
  for (int i = 0; i < TPW / 4; i++) {
    sa += (NSEG == 1 && i == 15) ? WREG - 15 * 1024 : 1024;
    uint32_t y[4];
#pragma unroll
    for (int u = 0; u < 4; u++) {
      s = cmad(lam, s, make_float2(bf_lo(v[u]), bf_hi(v[u])));
      y[u] = pack2(fmaf(coef.x, s.x, -coef.y * s.y), fmaf(-coef.x, s.y, -coef.y * s.x));
      v[u] = __shfl_xor_sync(~0u, y[u], 1);
    }
#pragma unroll
    for (int u = 0; u < 4; u++) {
      hg[u * 576] = __byte_perm(y[u], v[u], sel);
      v[u] = lds32((sa ^ (u << 5)) + u * 256);
    }
    hg += 4 * 576;
  }
  if (NSEG > 1) mbar_arrive_w(BAR_P1 + (v[0] & v[1] & v[2] & v[3] & zero));
  fence_async_all();
  __syncwarp();
}

__host__ __device__ constexpr int kb_tile(int kk) { return kk < 4 ? kk : kk == 4 ? 8 : kk - 1; }
template <int N>
__device__ __forceinline__ void mma_block(float (&acc)[N / 2], const uint32_t (&hr)[80], int kk, uint64_t da, uint32_t ba, bool first) {
  const uint64_t db = kk >= 9 ? desc_k(ba) : desc_mn(ba);
  const int oa = (kk < 4 ? 7 - kk : kk - 9) * (UNIT >> 4);
#pragma unroll
  for (int ks = 0; ks < 4; ks++) {
    const int sd = !(first && ks == 0);
    if (kk >= 9) {
      if constexpr (N == 128) wgmma_ss_n128<0>(acc, da, oa + ks * 2, db, ks * 2, sd); else wgmma_ss_n64<0>(acc, da, oa + ks * 2, db, ks * 2, sd);
    } else if (kk < 4) {
      if constexpr (N == 128) wgmma_ss_n128<1>(acc, da, oa + ks * 2, db, ks * 128, sd); else wgmma_ss_n64<1>(acc, da, oa + ks * 2, db, ks * 128, sd);
    } else {
      if constexpr (N == 128) wgmma_rs_n128<1>(acc, &hr[(kk - 4) * 16 + ks * 4], db, ks * 128, sd);
      else wgmma_rs_n64<1>(acc, &hr[(kk - 4) * 16 + ks * 4], db, ks * 128, sd);
    }
  }
}

__device__ __forceinline__ void spare_scan(const Params& p, int m, int r, int w8, int lane) {
  const uint32_t par = get_par();
  float2 lam, coef;
  ssm_coef(p, 512 + (w8 & 1) * 32 + lane, lam, coef);
  CPROBE(6 + 4 * r);
  bar_sync(5, 256);
  mbar_arrive_w(BAR_STASH);
  ssm_scan<4>(lam, coef, (w8 & 1) * 32 + lane, w8 >> 1, 8, m, par, p.zero);
  mbar_arrive_w(BAR_SCAN);
  CPROBE(7 + 4 * r);
}
__device__ __forceinline__ void spare_atom8(const Params& p, const uint32_t* tab, int m, int wg, int w8, int lane) {
  float acc[32];
  const uint32_t are = ring_get(tab[0], 150), aim = ring_get(tab[1], 150), cb = ring_get(tab[2], 150);
  mma_g8(acc, are + wg * 512, aim + wg * 512, cb);
  wg_wait<0>();
  ring_put(tab[0]); ring_put(tab[1]); ring_put(tab[2]);
  fence_regs(acc);
  uint32_t pk[16];
  pack_part(pk, acc, get_par());
#pragma unroll
  for (int i = 0; i < 4; i++) st_tag16(part_ptr(m, 8, 8) + w8 * 128 + lane + i * 32, &pk[4 * i]);
  CPROBE(21 + (m >> 2));
}

struct Who {
  int tid;
  __device__ __forceinline__ int wg() const { return tid >> 7; }
  __device__ __forceinline__ int w8() const { return tid >> 5; }
  __device__ __forceinline__ int lane() const { return tid & 31; }
  __device__ __forceinline__ int row() const { return (tid >> 5) * 16 + ((tid & 31) >> 2); }
  __device__ __forceinline__ uint32_t wb() const { return sb + (tid >> 7) * WREG; }
  __device__ __forceinline__ uint32_t frag() const { return (((tid >> 5) & 3) * 16 + (tid & 15)) * 128 + ((((tid >> 4) & 1) ^ (tid & 7)) << 4); }
};
__device__ __forceinline__ Who who() { Who w; asm volatile("mov.u32 %0, %%tid.x;" : "=r"(w.tid)); return w; }

__device__ __forceinline__ void consumer(const Params& p, bool spare, int m, int j) {
  const int wg = threadIdx.x >> 7;
  if (!spare) publish_stats(p.xg, m * 128 + j * 16 + (threadIdx.x >> 4), threadIdx.x & 31);
  bar_sync(6, 288);
  CPROBE(20);
  uint32_t hr[80];
  {
    uint32_t xa[144];
    float acc[64];
#pragma unroll 1
    for (int r = 0;; r++) {
      hand_over(6 - 5 * wg); hand_over(7 - 5 * wg); hand_over(9 - 5 * wg);
      uint32_t n[4];
      {
        const Who w = who();
        const uint32_t dep = load_x_frags(xa, n, w.wb() + w.frag(), BAR_X + wg * 24, r & 1, p.zero, g_stats + (m + 4 * r) * 128 + w.row(), w.row(), w.lane());
        hand_over(1 + 5 * wg, dep); hand_over(2 + 5 * wg, dep); hand_over(4 + 5 * wg, dep);
      }
      norm_blocks(xa, 0, AHEAD, n, 0);
      CPROBE(spare ? 5 + 4 * r : 1);
      tile_rs<0>(acc, xa, spare ? p.sched_sp + (r ? 12 * r - 3 : 0) : p.sched, wg, 2, 0, [&](int kb) {
        if (kb + AHEAD < 9) norm_blocks(xa, kb + AHEAD, kb + AHEAD + 1, n, who().tid & p.zero);
      });
      const Who w = who();
      stash_v(acc, w.wb(), w.row(), w.lane());
      if (!spare) break;
      spare_scan(p, m + 4 * r, r, w.w8(), w.lane());
#pragma unroll 1
      for (int q = r > 0 ? r - 1 : 1; q <= (r == 3 ? 3 : r - 1); q++) spare_atom8(p, p.sched_sp + 12 * q + (q < 3 ? 18 : 9), m + 4 * q, wg, w.w8(), w.lane());
      if (r == 3) { mbar_arrive_w(BAR_DONE); return; }
    }
    __syncwarp();
    mbar_arrive_w(BAR_STASH);
    CPROBE(2);
#pragma unroll 1
    for (int t = 0;; t++) {
      uint32_t ha;
      tile_rs<1>(acc, xa, p.sched + 9 + 9 * t, wg, 1 + (t & 1), 9 + 9 * t, [&](int kb) {
        if (kb < 8) return;
        const Who w = who();
        ha = w.wb() + w.frag();
        const uint32_t rc = p.reclaim[wg][t & 7];
        if (rc) mbar_wait(BAR_EMPTY + bar_of(rc), rc >> 31);
        if (t == 6) {
          mbar_wait(BAR_SCAN, 0);
          fence_async();
          bar_sync(3 + wg, 128);
        }
      });
      if (t == 8) {
        __syncwarp();
#pragma unroll
        for (int b = 0; b < 4; b++)
#pragma unroll
          for (int ks = 0; ks < 4; ks++) ldsm4(&hr[16 + b * 16 + ks * 4], (ha ^ (ks << 5)) + (3 - b) * UNIT);
        break;
      }
      ha += (7 - t) * UNIT;
#pragma unroll
      for (int ks = 0; ks < 4; ks++) {
        uint32_t h[4];
#pragma unroll
        for (int i = 0; i < 4; i++) h[i] = glu2(acc, ks * 4 + i);
        stsm4(ha ^ (ks << 5), h);
      }
      CPROBE(3 + t);
    }
#pragma unroll
    for (int i = 0; i < 16; i++) hr[i] = glu2(acc, i);
  }
  {
    uint32_t dep = 0;
#pragma unroll
    for (int i = 16; i < 80; i += 4) dep |= hr[i];
    dep &= p.zero;
    hand_over(0, dep); hand_over(5, dep); hand_over(1, dep); hand_over(6, dep);
  }
  CPROBE(11);
  const uint32_t par = get_par();
  uint4* const pb = part_ptr(m, 0, 0) + who().w8() * 128 + who().lane();
  auto src = [&](int d) { return pb + (j * 9 + ((j - d) & 7)) * 1024; };
  auto dst = [&](int d) { return pb + ((d ? (j + d) & 7 : 8) * 9 + j) * 1024; };
  const uint32_t* tab = p.sched + 90;
  const uint64_t da = desc_k(__shfl_sync(~0u, who().wb() >> 4, 0));
  float R[32];
  uint32_t pk[32];
#pragma unroll 1
  for (int ps = 0; ps < 4; ps++) {
    float acc[64];
    uint32_t prev = 0, prev2 = 0, ex = 0;
    if (wg == 1) bar_sync(2 - (ps & 1), 256);
#pragma unroll
    for (int kk = 0; kk < 11; kk++) {
      const uint32_t e = tab[kk], ba = ring_get(e, 90 + 11 * ps + kk);
      if (kk == 9 && ps == 0) mbar_wait(BAR_FULL + wg * 5 * 8, p.sched[NSLOT + wg] >> 31);
      wg_fence();
      mma_block<128>(acc, hr, kk, da, ba, kk == 0);
      wg_commit();
      if (kk == SKEW2 - 1 && wg == 0) bar_arrive(2 - (ps & 1), 256);
      uint32_t dep = 0;
      if (kk >= 6 && ps == 0) {
        if (kk == 6) {
          ex = ring_get(tab[7], 151);
          tab++;
          const Who w = who();
          const uint32_t xb = addr_of(ex) + wg * UNIT + w.frag();
#pragma unroll
          for (int ks = 0; ks < 4; ks++) {
            ldsm4(&pk[4 * ks], xb ^ (ks << 5));
            const uint2 d = lds64(OFF_DSK + ks * 32 + (w.lane() & 3) * 8);
            pk[16 + 2 * ks] = d.x; pk[17 + 2 * ks] = d.y;
          }
          const uint2 s0 = lds64(OFF_STATS + w.row() * 8), s1 = lds64(OFF_STATS + w.row() * 8 + 64);
          pk[24] = s0.x; pk[25] = s0.y; pk[26] = s1.x; pk[27] = s1.y;
        } else {
          const RowStat a = row_stat(make_uint2(pk[24], pk[25])), b = row_stat(make_uint2(pk[26], pk[27]));
          if (kk == 7) ring_put(ex, (pk[0] | pk[4] | pk[8] | pk[12]) & p.zero);
#pragma unroll
          for (int i = 4 * kk - 28; i < 4 * kk - 24; i++) {
            ((i & 1) ? b : a).resid(R[2 * i], R[2 * i + 1], pk[i], pk[16 + (i >> 1)]);
            dep |= __float_as_uint(R[2 * i]) | __float_as_uint(R[2 * i + 1]);
          }
          dep &= p.zero;
        }
      }
      if (kk < 8 && ps > 0) st_tag16(dst(2 * ps - 2 + (kk >> 2)) + (kk & 3) * 32, &pk[kk * 4]);
      if (kk == 6 && ps == 1) mbar_arrive_w(BAR_P1);
      if (ps > 1) {
        if (kk == 5) recv_issue(pk, src(2 * ps - 3));
        if (kk == 7) { recv_check(pk, src(2 * ps - 3), par); recv_add(R, pk, 0, 8); }
        if (kk == 8) { if (ps == 3) recv_issue(pk + 16, src(2)); recv_add(R, pk, 8, 16); }
        if (kk == 10 && ps == 3) { recv_check(pk + 16, src(2), par); recv_add(R, pk + 16, 0, 16); }
      }
      if (kk >= 2) { wg_wait<2>(); TR(88 + 11 * ps + kk, 2); ring_put(prev2, dep); }
      prev2 = prev; prev = e;
    }
    tab += 11;
    wg_wait<1>();
    ring_put(prev2);
    wg_wait<0>();
    TR(100 + 11 * ps, 2);
    ring_put(prev);
    fence_regs(acc);
    pack_part(pk, acc, par);
    CPROBE(12 + ps);
  }
  {
    float acc[32];
    uint32_t t[16];
    recv_issue(t, src(4));
#pragma unroll
    for (int i = 0; i < 8; i++) st_tag16(dst(6 + (i >> 2)) + (i & 3) * 32, &pk[i * 4]);
    if (wg == 1) bar_sync(2, 256);
    {
      const uint32_t are = ring_get(tab[0], 134), aim = ring_get(tab[1], 135), cb = ring_get(tab[2], 136);
      mma_g8(acc, are + wg * 512, aim + wg * 512, cb);
    }
#pragma unroll
    for (int s = 0; s < 6; s++) {
      const uint32_t ba = ring_get(tab[3 + s], 137 + s);
      wg_fence();
      mma_block<64>(acc, hr, 2 * s, da, ba, false);
      if (s < 5) mma_block<64>(acc, hr, 2 * s + 1, da, ba + 512, false);
      wg_commit();
      if (s == 0) {
        if (wg == 0) bar_arrive(2, 256);
        wg_wait<1>();
        ring_put(tab[0]);
      }
      if (s == 1) { recv_check(t, src(4), par); recv_add(R, t, 0, 16); recv_issue(t, src(5)); }
      if (s == 3) { recv_check(t, src(5), par); recv_add(R, t, 0, 16); }
      if (s == 5) { recv_issue(pk + 16, src(6)); recv_issue(pk, src(7)); }
    }
    CPROBE(28);
    wg_wait<0>();
    TR(142, 2);
    fence_regs(acc);
    CPROBE(16);
#pragma unroll
    for (int i = 0; i < 32; i++) R[i] += acc[i];
    recv_check(pk + 16, src(6), par);
    recv_check(pk, src(7), par);
#pragma unroll
    for (int i = 0; i < 16; i++) t[i] = hadd2(pk[16 + i], pk[i]);
    recv_add(R, t, 0, 16);
    CPROBE(29);
    const Who w = who();
    store_out(R, p.out + (size_t)(m * 128 + w.row()) * DM + j * 64, w.lane());
    mbar_arrive_w(BAR_DONE);
    CPROBE(17);
    TR(143, 0);
  }
}

__device__ __forceinline__ void load_x(const Params& p, int m, int wg, int g0, int g1) {
#pragma unroll 1
  for (int g = g0; g < g1; g++) {
    mbar_expect_tx(BAR_X + (wg * 3 + g) * 8, 3 * UNIT);
    tma_load3(sb + wg * WREG + g * 3 * UNIT, &p.x, 0, m * 128 + wg * 64, g * 3, BAR_X + (wg * 3 + g) * 8);
  }
}
__device__ __forceinline__ uint32_t slot_acquire(uint32_t e, uint32_t bytes) {
  const uint32_t bar = BAR_FULL + bar_of(e);
  if (!(e & 0x8000)) mbar_wait_b(bar + (BAR_EMPTY - BAR_FULL), (e >> 30) & 1);
  mbar_expect_tx(bar, bytes);
  return bar;
}
__device__ __forceinline__ void load_slot(uint32_t e, const CUtensorMap* m0, int a0, int b0, const CUtensorMap* m1, int a1, int b1) {
  const uint32_t dst = addr_of(e), bar = slot_acquire(e, m1 ? 2 * UNIT : UNIT);
  tma_load(dst, m0, a0, b0, bar);
  if (m1) tma_load(dst + UNIT, m1, a1, b1, bar);
}
__device__ __forceinline__ const CUtensorMap* p2_box(const Params& p, int j, int kk, int a, int& c0, int& c1) {
  if (kk >= 9) { c0 = 64 * j; c1 = 64 * a; return kk == 9 ? &p.cre : &p.cim; }
  c0 = 64 * a; c1 = DM * j + 64 * kb_tile(kk);
  return &p.wd;
}
__device__ __forceinline__ void load_g8(const Params& p, const uint32_t* tab, int m, int a) {
#pragma unroll 1
  for (int k = 0; k < 2; k++) load_slot(tab[k], &p.hs, 1024 + 64 * k, m * 128, &p.hs, 1024 + 64 * k, m * 128 + 64);
  load_slot(tab[2], &p.cre, 512, 64 * a, &p.cim, 512, 64 * a);
}
__device__ __forceinline__ void producer_main(const Params& p, int m, int j) {
  const uint32_t* tab = p.sched;
#pragma unroll 1
  for (int kb = 0; kb < 9; kb++) {
    load_slot(*tab++, &p.bre, 64 * kb, 64 * j, &p.bim, 64 * kb, 64 * j);
    if (kb == 0 && XPRI >= 0) mbar_wait_b(BAR_X + XPRI * 8, 0);
    if (XAT >= 0 && kb >= XAT && kb < XAT + 3) load_x(p, m, 1, kb - XAT, kb - XAT + 1);
    if (XAT < 0 && kb == 0) load_x(p, m, 1, 0, 3);
  }
  PROBE(3, 2);
#pragma unroll 1
  for (int c = DM * j; c < DM * j + DM; c += 64)
#pragma unroll 1
    for (int k = 0; k < DM; k += 64) load_slot(*tab++, &p.wg, c, k, &p.wu, c, k);
  mbar_wait_b(BAR_SCAN, 0);
  tma_prefetch(&p.x2, 64 * j, m * 128);
#pragma unroll 1
  for (int k = 0; k < 4; k++) tma_prefetch(&p.hs, 128 * j + 64 * (k & 1), m * 128 + 32 * (k & 2));
#pragma unroll 1
  for (int ps = 0; ps < 4; ps++)
#pragma unroll 1
    for (int kk = 0; kk < 11; kk++) {
      int a0, b0, a1, b1;
      const CUtensorMap* mp = p2_box(p, j, kk, ps == 0 ? 8 : (j + 2 * ps) & 7, a0, b0);
      p2_box(p, j, kk, (j + 2 * ps + 1) & 7, a1, b1);
      load_slot(*tab++, mp, a0, b0, mp, a1, b1);
      if (ps == 0) PROBE(3, 8 + kk);
      if (kk == 6 && ps == 0) {
        const uint32_t e = *tab++, bar = slot_acquire(e, 2 * UNIT);
        tma_load(addr_of(e), &p.x2, 64 * j, m * 128, bar);
#pragma unroll 1
        for (int w = 0; w < 2; w++) load_slot(p.sched[NSLOT + w], &p.hs, 128 * j, m * 128 + w * 64, &p.hs, 128 * j + 64, m * 128 + w * 64);
      }
    }
  mbar_wait_b(BAR_G8, 0);
  load_g8(p, tab, m, j);
  tab += 3;
#pragma unroll 1
  for (int s = 0; s < 6; s++) {
    int a0, b0, a1 = 0, b1 = 0;
    const CUtensorMap* m0 = p2_box(p, j, 2 * s, j, a0, b0);
    const CUtensorMap* m1 = s < 5 ? p2_box(p, j, 2 * s + 1, j, a1, b1) : nullptr;
    load_slot(*tab++, m0, a0, b0, m1, a1, b1);
  }
}
__device__ __forceinline__ void producer_spare(const Params& p, int s) {
  const uint32_t* tab = p.sched_sp;
  load_x(p, s, 1, 0, 3);
#pragma unroll 1
  for (int m = s; m < 16; m += 4) {
#pragma unroll 1
    for (int kb = 0; kb < 9; kb++) load_slot(*tab++, &p.bre, 64 * kb, 512, &p.bim, 64 * kb, 512);
    mbar_wait_b(BAR_STASH, (m >> 2) & 1);
    if (m < 12) { load_x(p, m + 4, 0, 1, 3); load_x(p, m + 4, 1, 1, 3); }
    if (m >= 4) { load_g8(p, tab, m - 4, 8); tab += 3; }
    mbar_wait_b(BAR_P1, (m >> 2) & 1);
    if (m < 12) { load_x(p, m + 4, 0, 0, 1); load_x(p, m + 4, 1, 0, 1); }
    mbar_wait_b(BAR_SCAN, (m >> 2) & 1);
  }
  load_g8(p, tab, s + 12, 8);
}

__device__ __forceinline__ void scan_worker(const Params& p, int m, int j, int c) {
  float2 lam, coef;
  ssm_coef(p, 64 * j + c, lam, coef);
  mbar_wait_b(BAR_STASH, 0);
  if (c == 0) PROBE(2, 1);
  ssm_scan<1>(lam, coef, c, 0, j, m, get_par(), 0);
  mbar_arrive_w(BAR_SCAN);
  if (c == 0) PROBE(2, 2);
}
template <int N>
__device__ __forceinline__ void sum_pieces(float (&v)[4], const uint2* src, uint32_t par) {
  uint2 a[N];
  uint32_t it = 0, bad;
  src += who().lane() * 2;
  while (true) {
    bad = 0;
#pragma unroll
    for (int i = 0; i < N; i++) a[i] = ld_tag8(src + i * 2048);
#pragma unroll
    for (int i = 0; i < N; i++) bad |= a[i].x ^ par;
    if (!__any_sync(~0u, bad & 1)) break;
    if (++it > (1u << 21)) __trap();
    __nanosleep(400);
  }
#pragma unroll
  for (int i = 0; i < N; i++) { v[0] += bf_lo(a[i].x); v[1] += bf_hi(a[i].x); v[2] += bf_lo(a[i].y); v[3] += bf_hi(a[i].y); }
}
__device__ __forceinline__ void reduce_atom8(const Params& p, int m, int j, int w) {
  mbar_wait_slow(BAR_P1, 0);
  const uint32_t par = get_par();
  if (w == 0) PROBE(2, 23);
#pragma unroll 1
  for (int c = w; c < 8; c += 3) {
    const uint2* src = reinterpret_cast<const uint2*>(part_ptr(m, 8, 0) + j * 128 + (c >> 1) * 32) + (c & 1);
    const size_t off = (size_t)(m * 128 + j * 16) * DM + 512 + 8 * c;
    float v[4] = {0.f, 0.f, 0.f, 0.f};
    sum_pieces<5>(v, src, par);
    if (w == 0) PROBE(2, 24 + (c / 3) * 2);
    uint32_t x0, x1;
    {
      const int l = who().lane();
      const uint32_t* xp = reinterpret_cast<const uint32_t*>(p.xg + off) + (l >> 2) * (DM / 2) + (l & 3);
      asm volatile("ld.global.nc.b32 %0, [%2];\nld.global.nc.b32 %1, [%2+9216];" : "=r"(x0), "=r"(x1) : "l"(xp));
    }
    sum_pieces<4>(v, src + 5 * 2048, par);
    if (w == 0) PROBE(2, 25 + (c / 3) * 2);
    const int l = who().lane();
    const uint32_t d2 = lds32(OFF_DSK + 128 + c * 16 + (l & 3) * 4), sa = OFF_STATS + (j * 16 + (l >> 2)) * 8;
    float a, b;
    row_stat(lds64(sa)).resid(a, b, x0, d2);
    v[0] += a; v[1] += b;
    row_stat(lds64(sa + 64)).resid(a, b, x1, d2);
    float2* o = reinterpret_cast<float2*>(p.out + off) + (l >> 2) * (DM / 2) + (l & 3);
    __stcs(o, make_float2(v[0], v[1]));
    __stcs(o + 4 * DM, make_float2(v[2] + a, v[3] + b));
  }
  if (w == 0) PROBE(2, 5);
}
__device__ __forceinline__ void prefetch_weights(const Params& p, int m, int j) {
  mbar_wait_b(BAR_X + 5 * 8, 0);
#pragma unroll 1
  for (int n = m; n < 162; n += 16) {
    tma_prefetch((n & 1) ? &p.wu : &p.wg, DM * j + 64 * (n / 18), 64 * ((n % 18) >> 1));
    __nanosleep(500);
  }
#pragma unroll 1
  for (int n = m; n < 101; n += 16) {
    const int a = n / 11;
    int c0, c1;
    const CUtensorMap* mp = p2_box(p, n < 99 ? j : 8, n < 99 ? n % 11 : n - 90, n >= 99 ? j : a ? (j + a) & 7 : 8, c0, c1);
    tma_prefetch(mp, c0, c1);
    __nanosleep(1000);
  }
}

__global__ void __launch_bounds__(NTHREADS, 1) fused_kernel(const __grid_constant__ Params p) {
  extern __shared__ __align__(1024) uint8_t smem[];
  const int tid = threadIdx.x, lane = tid & 31;
  const bool spare = blockIdx.x >= 128;
  const int b = (spare || !MAPB) ? blockIdx.x : (blockIdx.x & 0x70) | ((blockIdx.x & 1) << 3) | ((blockIdx.x >> 1) & 7);
  const int m = spare ? b - 128 : b >> 3, j = b & 7;
  if (tid < 256) {
    asm volatile("setmaxnreg.inc.sync.aligned.u32 240;");
    CPROBE(0);
    TR(145, 0);
    consumer(p, spare, m, j);
  } else {
    asm volatile("setmaxnreg.dec.sync.aligned.u32 24;");
    if (__shfl_sync(~0u, tid >> 5, 0) == 8) {
      if (lane == 0) {
        PROBE(3, 0);
#pragma unroll
        for (int i = 0; i < 6; i++) mbar_init(BAR_X + i * 8, 1);
        fence_init();
      }
      __syncwarp();
      load_x(p, m, 0, 0, 3);
      PROBE(3, 4);
    } else if (tid == 288) {
#pragma unroll
      for (int i = 0; i < 14; i++) mbar_init(BAR_FULL + i * 8, 1);
      fence_init();
    } else if (tid == 320) {
#pragma unroll
      for (int i = 0; i < 14; i++) mbar_init(BAR_EMPTY + i * 8, 8);
      fence_init();
    } else if (tid == 352) {
      if ((uint32_t)__cvta_generic_to_shared(smem) != sb) __trap();
      mbar_init(BAR_STASH, 8); mbar_init(BAR_P1, 8); mbar_init(BAR_SCAN, spare ? 8 : 2); mbar_init(BAR_G8, 1); mbar_init(BAR_PAR, 1); mbar_init(BAR_DONE, 8);
      fence_init();
    }
    bar_sync(0, 128);
    const int aw = __shfl_sync(~0u, who().w8(), 0);
    if (aw == 10) bar_arrive(6, 288);
    if (aw == 8) {
      PROBE(3, 3);
      if (!spare) producer_main(p, b >> 3, j); else producer_spare(p, b & 3);
    } else if (aw < 11) {
      if (!spare) {
        scan_worker(p, b >> 3, j, tid - 288);
        reduce_atom8(p, b >> 3, j, __shfl_sync(~0u, who().w8(), 0) - 9);
      } else if (tid == 288) {
#pragma unroll 1
        for (int r = 0; r < 4; r++) {
          mbar_wait_b(BAR_SCAN, r & 1);
          asm volatile("st.release.gpu.global.b32 [%0], %1;" ::"l"(g_flag + (b & 3) + 4 * r), "r"(get_par()) : "memory");
        }
      }
    } else {
      const uint32_t ep = g_epoch[blockIdx.x] + 1;
      const uint32_t d = reinterpret_cast<const uint32_t*>(p.dskip)[32 * j + lane], d8 = reinterpret_cast<const uint32_t*>(p.dskip)[256 + lane];
      if (b < 80) tma_prefetch((b & 8) ? &p.bim : &p.bre, 64 * (4 + (b >> 4)), 64 * j);
      if (lane < 10) asm volatile("prefetch.tensormap [%0];" ::"l"(&p.x + lane) : "memory");
      if (lane == 0) sts32(OFF_PAR, ep & 1);
      sts32(OFF_DSK + (lane & 24) * 4 + (lane & 3) * 8 + (lane & 4), hadd2(d, d)); sts32(OFF_DSK + 128 + lane * 4, hadd2(d8, d8));
      __syncwarp();
      if (lane == 0) { mbar_arrive(BAR_PAR); if (spare) g_epoch[blockIdx.x] = ep; }
      __syncwarp();
      if (!spare) {
        prefetch_weights(p, b >> 3, j);
        mbar_wait_slow(BAR_P1, 0);
        if (lane == 0) g_epoch[blockIdx.x] = ep;
        uint32_t f, it = 0;
        while (true) {
          asm volatile("ld.acquire.gpu.global.b32 %0, [%1];" : "=r"(f) : "l"(g_flag + (b >> 3)) : "memory");
          if (f == (ep & 1)) break;
          if (++it > (1u << 21)) __trap();
          __nanosleep(300);
        }
        fence_async_all();
        mbar_arrive_w(BAR_G8);
        reduce_atom8(p, b >> 3, j, 2);
      }
      if (lane == 0) mbar_wait_b(BAR_DONE, 0);
      __syncwarp();
      PROF_DUMP();
    }
  }
}

typedef CUresult (*EncodeFn)(CUtensorMap*, CUtensorMapDataType, cuuint32_t, void*, const cuuint64_t*, const cuuint64_t*, const cuuint32_t*,
                             const cuuint32_t*, CUtensorMapInterleave, CUtensorMapSwizzle, CUtensorMapL2promotion, CUtensorMapFloatOOBfill);

void make_map(EncodeFn fn, CUtensorMap* map, const void* ptr, int rows, int cols, int box_rows = 64, int kblocks = 0) {
  cuuint64_t dims[3] = {(cuuint64_t)(kblocks ? 64 : cols), (cuuint64_t)rows, (cuuint64_t)(cols / 64)}, strides[2] = {(cuuint64_t)cols * 2, 128};
  cuuint32_t box[3] = {64, (cuuint32_t)box_rows, (cuuint32_t)kblocks}, es[3] = {1, 1, 1};
  fn(map, CU_TENSOR_MAP_DATA_TYPE_BFLOAT16, kblocks ? 3 : 2, const_cast<void*>(ptr), dims, strides, box, es, CU_TENSOR_MAP_INTERLEAVE_NONE,
     CU_TENSOR_MAP_SWIZZLE_128B, CU_TENSOR_MAP_L2_PROMOTION_L2_128B, CU_TENSOR_MAP_FLOAT_OOB_FILL_NONE);
}

struct Win { int pair, from, until; };
struct RingSim {
  int rel[14] = {0}, uses[14] = {0}, last[14];
  RingSim() { for (int i = 0; i < 14; i++) last[i] = -100 + i; }
  uint32_t take(int pr, int i) {
    const int n = rel[pr];
    const uint32_t e = pair_e(pr) | ((uint32_t)(uses[pr] & 1) << 31) | (n == 0 ? 0x8000u : ((uint32_t)((n - 1) & 1) << 30));
    uses[pr]++; rel[pr]++; last[pr] = i;
    return e;
  }
  uint32_t next(const Win* win, int nwin, int i) {
    int best = -1;
    for (int w = 0; w < nwin; w++) {
      if (i == win[w].from && win[w].pair < 10) rel[win[w].pair]++;
      if (i >= win[w].from && i <= win[w].until && (best < 0 || last[win[w].pair] < last[best])) best = win[w].pair;
    }
    return take(best, i);
  }
};
void make_schedule(Params& p) {
  const Win win[] = {
    {10, 0, 999}, {11, 0, 999}, {12, 0, 999}, {13, 0, 999}, {4, 4, 999}, {9, 7, 999},
    {2, 4, 32}, {7, 7, 32},
    {1, 4, 50}, {6, 7, 50},
    {1, 96, 999}, {6, 96, 999},
  };
  RingSim r;
  for (int i = 0; i < NSLOT; i++) {
    p.sched[i] = r.next(win, sizeof(win) / sizeof(win[0]), i);
    if (i >= 17 && i < 89 && (i - 17) % 9 == 0)
      for (int w = 0, t = (i - 17) / 9; w < 2; w++) {
        const int pr = w * 5 + (7 - t) / 2;
        p.reclaim[w][t] = r.uses[pr] > 0 ? pair_e(pr) | ((uint32_t)((r.rel[pr] - 1) & 1) << 31) : 0;
      }
  }
  for (int w = 0; w < 2; w++) { r.rel[5 * w]++; p.sched[NSLOT + w] = r.take(5 * w, NSLOT); }
  Win ws[28] = {{10, 0, 999}, {11, 0, 999}, {12, 0, 999}, {13, 0, 999}};
  for (int k = 0; k < 24; k++) ws[4 + k] = Win{(k & 1) * 5 + (k % 6 < 2 ? 1 : k % 6 < 4 ? 2 : 4), (k < 6 ? 4 : 12 * (k / 6) + 1), (k < 6 ? 8 : 12 * (k / 6) + 5)};
  RingSim q;
  for (int i = 0; i < NSLOT_SP; i++) p.sched_sp[i] = q.next(ws, 28, i);
}

}

extern "C" void kernel_launch(void* const* d_in, const int* in_sizes, int n_in, void* d_out, int out_size) {
  static EncodeFn fn = nullptr;
  static void* hs = nullptr;
  if (!fn) {
    void* f = nullptr;
    cudaDriverEntryPointQueryResult qr;
    cudaGetDriverEntryPoint("cuTensorMapEncodeTiled", &f, cudaEnableDefault, &qr);
    fn = (EncodeFn)f;
    cudaGetSymbolAddress(&hs, g_hs);
    cudaFuncSetAttribute(fused_kernel, cudaFuncAttributeMaxDynamicSharedMemorySize, SMEM_BYTES);
  }
  Params p;
  make_map(fn, &p.x, d_in[0], SEQ, DM, 64, 3);
  make_map(fn, &p.x2, d_in[0], SEQ, DM, 128);
  make_map(fn, &p.bre, d_in[3], DM, DM);
  make_map(fn, &p.bim, d_in[4], DM, DM);
  make_map(fn, &p.cre, d_in[5], DM, DM);
  make_map(fn, &p.cim, d_in[6], DM, DM);
  make_map(fn, &p.wg, d_in[10], DM, FF);
  make_map(fn, &p.wu, d_in[11], DM, FF);
  make_map(fn, &p.wd, d_in[12], FF, DM);
  make_map(fn, &p.hs, hs, SEQ, 1152);
  p.xg = (const __nv_bfloat16*)d_in[0];
  p.lam_re = (const __nv_bfloat16*)d_in[1];
  p.lam_im = (const __nv_bfloat16*)d_in[2];
  p.log_dt = (const __nv_bfloat16*)d_in[7];
  p.dskip = (const __nv_bfloat16*)d_in[8];
  p.out = (float*)d_out;
  p.zero = 0;
  make_schedule(p);
  fused_kernel<<<132, NTHREADS, SMEM_BYTES>>>(p);
}
```
